```python
import torch

def _softmax(x, axis=-1):
    return torch.softmax(x, dim=axis)
def _gelu(x):
    return torch.nn.functional.gelu(x, approximate="tanh")
def _silu(x):
    return torch.nn.functional.silu(x)
def _sigmoid(x):
    return torch.sigmoid(x)
def _layernorm(x, axis=-1, eps=1e-5):
    m = x.mean(dim=axis, keepdim=True)
    v = x.var(dim=axis, keepdim=True, unbiased=False)
    return (x - m) / torch.sqrt(v + eps)
def _scatter_add(tgt, idx, src, axis=0):
    return tgt.clone().index_add_(axis, idx, src)
def _segment_sum(src, seg, n):
    out = torch.zeros((n,) + src.shape[1:], dtype=src.dtype)
    return out.index_add_(0, seg, src)
def _pad(x, pw):
    flat = tuple(v for pair in reversed(pw) for v in pair)
    return torch.nn.functional.pad(x, flat)

kernel_name = 'recurrent_scan__ssm_conv_h3__swiglu_ffn__prompt'

def setup_inputs():

    _w = (lambda a: (lambda t: t.to(torch.bfloat16) if t.is_floating_point() else t)(torch.as_tensor(a)))
    def _A_setup():
        B, S, D = 1, 2048, 1024
        ks = 4
        return {
            "q": _w((lambda *s: torch.randn(*s, dtype=torch.bfloat16) * 0.05)(B, S, D)),
            "k": _w((lambda *s: torch.randn(*s, dtype=torch.bfloat16) * 0.2)(B, S, D)),
            "v": _w((lambda *s: torch.randn(*s, dtype=torch.bfloat16) * 0.2)(B, S, D)),
            "shift_k": _w((lambda *s: torch.randn(*s, dtype=torch.bfloat16) * 0.2)(D, ks) * 0.5),
            "ssm_k": _w((lambda *s: torch.randn(*s, dtype=torch.bfloat16) * 0.2)(D, S) * (1.0 / S ** 0.5)),
            "ssm_D": _w((lambda *s: torch.randn(*s, dtype=torch.bfloat16) * 0.2)(D)),
        }
    _A_in = _A_setup()

    def _B_setup():
        B, S, D, F = 1, 2048, 1024, 3584
        return {
            "x": _w((lambda *s: torch.randn(*s, dtype=torch.bfloat16) * 0.05)(B, S, D)),
            "w_gate": _w((lambda *s: torch.randn(*s, dtype=torch.bfloat16) * 0.1)(D, F)),
            "w_up": _w((lambda *s: torch.randn(*s, dtype=torch.bfloat16) * 0.1)(D, F)),
            "w_down": _w((lambda *s: torch.randn(*s, dtype=torch.bfloat16) * 0.1)(F, D)),
        }
    _B_in = _B_setup()

    return {
        "A_q": _A_in["q"],
        "A_k": _A_in["k"],
        "A_v": _A_in["v"],
        "A_shift_k": _A_in["shift_k"],
        "A_ssm_k": _A_in["ssm_k"],
        "A_ssm_D": _A_in["ssm_D"],
        "B_x": _B_in["x"],
        "B_w_gate": _B_in["w_gate"],
        "B_w_up": _B_in["w_up"],
        "B_w_down": _B_in["w_down"],
    }

def reference(A_q, A_k, A_v, A_shift_k, A_ssm_k, A_ssm_D, B_x, B_w_gate, B_w_up, B_w_down):
    def _A_ref(q, k, v, shift_k, ssm_k, ssm_D):
        B, S, D = q.shape
        ks = shift_k.shape[-1]
        k_pad = _pad(k, ((0, 0), (ks - 1, 0), (0, 0)))
        k_shift = torch.zeros_like(k)
        for t in range(ks):
            k_shift = k_shift + k_pad[:, t:t + S, :] * shift_k[:, ks - 1 - t][None, None, :]
        kv = k_shift * v
        L = 2 * S
        kv_pad = _pad(kv, ((0, 0), (0, S), (0, 0)))
        kf_pad = _pad(ssm_k, ((0, 0), (0, S)))
        kv_f = (lambda x, axes=(-2,-1): torch.fft.rfft2(x.float(), dim=axes))(kv_pad[:, None, :, :], axes=(1, 2))
        kf_f = (lambda x, axes=(-2,-1): torch.fft.rfft2(x.float(), dim=axes))(kf_pad[:, None, :], axes=(1, 2))
        kf_f = (lambda x, *d: x.permute(*d))(kf_f, 1, 2, 0)
        y_f = kv_f * kf_f[None, :, :, :]
        y = (lambda x, s, axes=(-2,-1): torch.fft.irfft2(x, s=s, dim=axes).to(torch.bfloat16))(y_f, (1, L), axes=(1, 2))[:, 0, :S, :]
        y = y + kv * ssm_D[None, None, :]
        return q * y

    def _B_ref(x, w_gate, w_up, w_down):
        g = _silu(x @ w_gate)
        u = x @ w_up
        return (g * u) @ w_down

    x = A_q
    xn = _layernorm(x, axis=-1)
    s = _A_ref(xn, A_k, A_v, A_shift_k, A_ssm_k, A_ssm_D)
    g = _silu(_B_ref(xn, B_w_gate, B_w_up, B_w_down))
    return x + s * g
```

```cpp
#include <cuda_runtime.h>
#include <cuda_bf16.h>
#include <cuda.h>
#include <stdint.h>
#include <stdio.h>

namespace h3 {

typedef __nv_bfloat16 bf16;
typedef __nv_bfloat162 bf162;

constexpr int S = 2048;
constexpr int D = 1024;
constexpr int F = 3584;
constexpr int NCTA = 128;

__device__ __align__(1024) bf16 g_xn[S * D];
__device__ __align__(1024) bf16 g_kvT[D * S];
__device__ __align__(1024) bf16 g_h[S * F];
__device__ __align__(1024) bf16 g_y2T[D * S];
constexpr int FLAG_STRIDE = 32;
constexpr int FL_XN = 0, FL_H = 16, FL_Y = 32, FL_KV = 40, FL_DONE = 41, FL_COUNT = 42;
__device__ __align__(1024) unsigned g_flags[FL_COUNT * FLAG_STRIDE];

struct alignas(64) Params {
    CUtensorMap tmXn128;
    CUtensorMap tmXn64;
    CUtensorMap tmWg2;
    CUtensorMap tmWu2;
    CUtensorMap tmWg1;
    CUtensorMap tmWu1;
    CUtensorMap tmH64;
    CUtensorMap tmWd;
    CUtensorMap tmX128;
    CUtensorMap tmY2T;
    CUtensorMap tmOut64;
    const bf16* q; const bf16* k; const bf16* v; const bf16* shift_k; const bf16* ssm_k; const bf16* ssm_D;
    bf16* xn; bf16* kvT; bf16* y2T;
    unsigned* flags;
    long long* dbg;
};

constexpr uint32_t RING_BYTES = 196608;
constexpr uint32_t A_STAGE = 49152, B_STAGE = 32768;
constexpr uint32_t OFF_STG = RING_BYTES;
constexpr uint32_t OFF_BAR = OFF_STG + 32768;
constexpr uint32_t BAR_FULLA = 0, BAR_EMPTYA = 32, BAR_FINALA = 64, BAR_FULLB = 96, BAR_EMPTYB = 144, BAR_Q = 192,
                   BAR_STGFULL = 200, BAR_STGEMPTY = 216, BAR_YFULL = 232, OFF_ZERO = 240;
constexpr uint32_t SMEM_BYTES = OFF_BAR + 256 + 1024;

constexpr int E_CONV_H = 16, E_CONV_U = 17, E_CONV_A = 18, E_CONV_B = 19, E_G2 = 20, E_EPI_X = 76, E_EPI_XN = 77, E_EPI_Y = 78;

__device__ __forceinline__ uint32_t smem_u32(const void* p) { return (uint32_t)__cvta_generic_to_shared(p); }
__device__ __forceinline__ uint64_t make_desc(uint32_t addr, uint32_t lbo, uint32_t sbo) {
    uint64_t d = (uint64_t)((addr & 0x3FFFF) >> 4);
    d |= (uint64_t)((lbo & 0x3FFFF) >> 4) << 16;
    d |= (uint64_t)((sbo & 0x3FFFF) >> 4) << 32;
    d |= (uint64_t)1 << 62;
    return d;
}
constexpr uint32_t WAIT_LIMIT = 1u << 27;
__device__ __forceinline__ void mbar_init(uint32_t bar, uint32_t count) { asm volatile("mbarrier.init.shared::cta.b64 [%0], %1;" :: "r"(bar), "r"(count) : "memory"); }
__device__ __forceinline__ void mbar_expect_tx(uint32_t bar, uint32_t bytes) { asm volatile("mbarrier.arrive.expect_tx.shared::cta.b64 _, [%0], %1;" :: "r"(bar), "r"(bytes) : "memory"); }
__device__ __forceinline__ void mbar_arrive(uint32_t bar) { asm volatile("mbarrier.arrive.shared::cta.b64 _, [%0];" :: "r"(bar) : "memory"); }
__device__ __forceinline__ void mbar_arrive_cta(uint32_t bar, uint32_t cta) {
    asm volatile("{\n.reg .b32 ra;\nmapa.shared::cluster.u32 ra, %0, %1;\nmbarrier.arrive.shared::cluster.b64 _, [ra];\n}" :: "r"(bar), "r"(cta) : "memory");
}
__device__ __forceinline__ uint32_t mbar_try(uint32_t bar, uint32_t parity) {
    uint32_t ok;
    asm volatile("{\n.reg .pred p;\nmbarrier.try_wait.parity.shared::cta.b64 p, [%1], %2;\nselp.u32 %0, 1, 0, p;\n}" : "=r"(ok) : "r"(bar), "r"(parity) : "memory");
    return ok;
}
__device__ __forceinline__ void mbar_wait(uint32_t bar, uint32_t parity) {
    if (!mbar_try(bar, parity)) {
        const uint32_t t0 = (uint32_t)clock();
        while (!mbar_try(bar, parity) && (uint32_t)clock() - t0 < WAIT_LIMIT) {}
    }
}
__device__ __forceinline__ void flag_wait(const unsigned* f, unsigned target) {
    const uint32_t t0 = (uint32_t)clock();
    unsigned v;
    do {
        asm volatile("ld.acquire.gpu.global.u32 %0, [%1];" : "=r"(v) : "l"(f) : "memory");
    } while (v < target && (uint32_t)clock() - t0 < WAIT_LIMIT);
    asm volatile("fence.proxy.async;" ::: "memory");
}
__device__ __forceinline__ void flag_add(unsigned* f) {
    asm volatile("red.release.gpu.global.add.u32 [%0], 1;" :: "l"(f) : "memory");
}
__device__ __forceinline__ void cluster_arrive() { asm volatile("barrier.cluster.arrive.release;" ::: "memory"); }
__device__ __forceinline__ void cluster_wait() { asm volatile("barrier.cluster.wait.acquire;" ::: "memory"); }
__device__ __forceinline__ void tma_2d(uint32_t dst, const CUtensorMap* m, int c0, int c1, uint32_t bar) {
    asm volatile("cp.async.bulk.tensor.2d.shared::cluster.global.mbarrier::complete_tx::bytes [%0], [%1, {%3, %4}], [%2];"
        :: "r"(dst), "l"(m), "r"(bar), "r"(c0), "r"(c1) : "memory");
}
__device__ __forceinline__ void tma_2d_mc(uint32_t dst, const CUtensorMap* m, int c0, int c1, uint32_t bar) {
    asm volatile("cp.async.bulk.tensor.2d.shared::cluster.global.mbarrier::complete_tx::bytes.multicast::cluster [%0], [%1, {%3, %4}], [%2], %5;"
        :: "r"(dst), "l"(m), "r"(bar), "r"(c0), "r"(c1), "h"((uint16_t)3) : "memory");
}
__device__ __forceinline__ void tma_3d(uint32_t dst, const CUtensorMap* m, int c0, int c1, int c2, uint32_t bar) {
    asm volatile("cp.async.bulk.tensor.3d.shared::cluster.global.mbarrier::complete_tx::bytes [%0], [%1, {%3, %4, %5}], [%2];"
        :: "r"(dst), "l"(m), "r"(bar), "r"(c0), "r"(c1), "r"(c2) : "memory");
}
__device__ __forceinline__ void bulk_g2s(uint32_t dst, const void* src, uint32_t bytes, uint32_t bar) {
    asm volatile("cp.async.bulk.shared::cluster.global.mbarrier::complete_tx::bytes [%0], [%1], %2, [%3];"
        :: "r"(dst), "l"(src), "r"(bytes), "r"(bar) : "memory");
}
__device__ __forceinline__ void bulk_s2g(void* dst, uint32_t src, uint32_t bytes) {
    asm volatile("cp.async.bulk.global.shared::cta.bulk_group [%0], [%1], %2;" :: "l"(dst), "r"(src), "r"(bytes) : "memory");
}
__device__ __forceinline__ void tma_store_2d(const CUtensorMap* m, uint32_t src, int c0, int c1) {
    asm volatile("cp.async.bulk.tensor.2d.global.shared::cta.bulk_group [%0, {%2, %3}], [%1];"
        :: "l"(m), "r"(src), "r"(c0), "r"(c1) : "memory");
}
__device__ __forceinline__ void bulk_commit() { asm volatile("cp.async.bulk.commit_group;" ::: "memory"); }
__device__ __forceinline__ void bulk_wait_read() { asm volatile("cp.async.bulk.wait_group.read 0;" ::: "memory"); }
__device__ __forceinline__ void bulk_wait_all() { asm volatile("cp.async.bulk.wait_group 0;" ::: "memory"); }
__device__ __forceinline__ void fence_async_smem() { asm volatile("fence.proxy.async.shared::cta;" ::: "memory"); }
__device__ __forceinline__ void prefetch_tmap(const CUtensorMap* m) { asm volatile("prefetch.tensormap [%0];" :: "l"(m) : "memory"); }
__device__ __forceinline__ void bar_sync(int id, int n) { asm volatile("bar.sync %0, %1;" :: "r"(id), "r"(n) : "memory"); }
__device__ __forceinline__ void cluster_sync() {
    asm volatile("barrier.cluster.arrive.release.aligned;" ::: "memory");
    asm volatile("barrier.cluster.wait.acquire.aligned;" ::: "memory");
}
__device__ __forceinline__ void wg_fence() { asm volatile("wgmma.fence.sync.aligned;" ::: "memory"); }
__device__ __forceinline__ void wg_commit() { asm volatile("wgmma.commit_group.sync.aligned;" ::: "memory"); }
template <int N> __device__ __forceinline__ void wg_wait() { asm volatile("wgmma.wait_group.sync.aligned %0;" :: "n"(N) : "memory"); }

#define H3_R4(b)  "+f"(d[b+0]), "+f"(d[b+1]), "+f"(d[b+2]), "+f"(d[b+3])
#define H3_R8(b)  H3_R4(b), H3_R4(b+4)
#define H3_R16(b) H3_R8(b), H3_R8(b+8)
#define H3_R32(b) H3_R16(b), H3_R16(b+16)
#define H3_R64(b) H3_R32(b), H3_R32(b+32)

__device__ __forceinline__ void wgmma_256(float (&d)[128], uint64_t a, uint64_t b, int scale_d) {
    asm volatile("{\n.reg .pred p;\nsetp.ne.b32 p, %130, 0;\n"
    "wgmma.mma_async.sync.aligned.m64n256k16.f32.bf16.bf16 "
    "{%0,%1,%2,%3,%4,%5,%6,%7,%8,%9,%10,%11,%12,%13,%14,%15,"
    "%16,%17,%18,%19,%20,%21,%22,%23,%24,%25,%26,%27,%28,%29,%30,%31,"
    "%32,%33,%34,%35,%36,%37,%38,%39,%40,%41,%42,%43,%44,%45,%46,%47,"
    "%48,%49,%50,%51,%52,%53,%54,%55,%56,%57,%58,%59,%60,%61,%62,%63,"
    "%64,%65,%66,%67,%68,%69,%70,%71,%72,%73,%74,%75,%76,%77,%78,%79,"
    "%80,%81,%82,%83,%84,%85,%86,%87,%88,%89,%90,%91,%92,%93,%94,%95,"
    "%96,%97,%98,%99,%100,%101,%102,%103,%104,%105,%106,%107,%108,%109,%110,%111,"
    "%112,%113,%114,%115,%116,%117,%118,%119,%120,%121,%122,%123,%124,%125,%126,%127},"
    "%128, %129, p, 1, 1, 0, 1;\n}\n"
    : H3_R64(0), H3_R64(64)
    : "l"(a), "l"(b), "r"(scale_d));
}
__device__ __forceinline__ void wgmma_128(float (&d)[64], uint64_t a, uint64_t b, int scale_d) {
    asm volatile("{\n.reg .pred p;\nsetp.ne.b32 p, %66, 0;\n"
    "wgmma.mma_async.sync.aligned.m64n128k16.f32.bf16.bf16 "
    "{%0,%1,%2,%3,%4,%5,%6,%7,%8,%9,%10,%11,%12,%13,%14,%15,"
    "%16,%17,%18,%19,%20,%21,%22,%23,%24,%25,%26,%27,%28,%29,%30,%31,"
    "%32,%33,%34,%35,%36,%37,%38,%39,%40,%41,%42,%43,%44,%45,%46,%47,"
    "%48,%49,%50,%51,%52,%53,%54,%55,%56,%57,%58,%59,%60,%61,%62,%63},"
    "%64, %65, p, 1, 1, 0, 1;\n}\n"
    : H3_R64(0)
    : "l"(a), "l"(b), "r"(scale_d));
}
__device__ __forceinline__ void mma_16816(float (&d)[4], uint32_t a0, uint32_t a1, uint32_t a2, uint32_t a3, uint32_t b0, uint32_t b1) {
    asm volatile("mma.sync.aligned.m16n8k16.row.col.f32.bf16.bf16.f32 {%0,%1,%2,%3}, {%4,%5,%6,%7}, {%8,%9}, {%0,%1,%2,%3};"
        : "+f"(d[0]), "+f"(d[1]), "+f"(d[2]), "+f"(d[3])
        : "r"(a0), "r"(a1), "r"(a2), "r"(a3), "r"(b0), "r"(b1));
}
__device__ __forceinline__ void ldsm_x4(uint32_t addr, uint32_t& r0, uint32_t& r1, uint32_t& r2, uint32_t& r3) {
    asm volatile("ldmatrix.sync.aligned.m8n8.x4.shared.b16 {%0,%1,%2,%3}, [%4];" : "=r"(r0), "=r"(r1), "=r"(r2), "=r"(r3) : "r"(addr) : "memory");
}
__device__ __forceinline__ void ldsm_x4_t(uint32_t addr, uint32_t& r0, uint32_t& r1, uint32_t& r2, uint32_t& r3) {
    asm volatile("ldmatrix.sync.aligned.m8n8.x4.trans.shared.b16 {%0,%1,%2,%3}, [%4];" : "=r"(r0), "=r"(r1), "=r"(r2), "=r"(r3) : "r"(addr) : "memory");
}
__device__ __forceinline__ void stsm_x4(uint32_t addr, uint32_t r0, uint32_t r1, uint32_t r2, uint32_t r3) {
    asm volatile("stmatrix.sync.aligned.m8n8.x4.shared.b16 [%0], {%1,%2,%3,%4};" :: "r"(addr), "r"(r0), "r"(r1), "r"(r2), "r"(r3) : "memory");
}
__device__ __forceinline__ void stsm_x4_t(uint32_t addr, uint32_t r0, uint32_t r1, uint32_t r2, uint32_t r3) {
    asm volatile("stmatrix.sync.aligned.m8n8.x4.trans.shared.b16 [%0], {%1,%2,%3,%4};" :: "r"(addr), "r"(r0), "r"(r1), "r"(r2), "r"(r3) : "memory");
}
template <int OFF> __device__ __forceinline__ uint32_t lds32_o(uint32_t addr) { uint32_t v; asm volatile("ld.shared.b32 %0, [%1+%2];" : "=r"(v) : "r"(addr), "n"(OFF) : "memory"); return v; }
template <int OFF> __device__ __forceinline__ void ldsm_x4_o(uint32_t addr, uint32_t& r0, uint32_t& r1, uint32_t& r2, uint32_t& r3) {
    asm volatile("ldmatrix.sync.aligned.m8n8.x4.shared.b16 {%0,%1,%2,%3}, [%4+%5];" : "=r"(r0), "=r"(r1), "=r"(r2), "=r"(r3) : "r"(addr), "n"(OFF) : "memory");
}
__device__ __forceinline__ uint32_t lds32(uint32_t addr) { uint32_t v; asm volatile("ld.shared.b32 %0, [%1];" : "=r"(v) : "r"(addr) : "memory"); return v; }
__device__ __forceinline__ uint4 lds128(uint32_t addr) { uint4 v; asm volatile("ld.shared.v4.b32 {%0,%1,%2,%3}, [%4];" : "=r"(v.x), "=r"(v.y), "=r"(v.z), "=r"(v.w) : "r"(addr) : "memory"); return v; }
__device__ __forceinline__ void sts128(uint32_t addr, uint32_t a, uint32_t b, uint32_t c, uint32_t d) { asm volatile("st.shared.v4.b32 [%0], {%1,%2,%3,%4};" :: "r"(addr), "r"(a), "r"(b), "r"(c), "r"(d) : "memory"); }

__device__ __forceinline__ uint32_t bf2_mul(uint32_t a, uint32_t b) { uint32_t r; asm("mul.rn.bf16x2 %0, %1, %2;" : "=r"(r) : "r"(a), "r"(b)); return r; }
__device__ __forceinline__ uint32_t bf2_add(uint32_t a, uint32_t b) { uint32_t r; asm("add.rn.bf16x2 %0, %1, %2;" : "=r"(r) : "r"(a), "r"(b)); return r; }
__device__ __forceinline__ uint32_t bf2_sub(uint32_t a, uint32_t b) { uint32_t r; asm("sub.rn.bf16x2 %0, %1, %2;" : "=r"(r) : "r"(a), "r"(b)); return r; }
__device__ __forceinline__ uint32_t pack_bf2(float lo, float hi) { uint32_t r; asm("cvt.rn.bf16x2.f32 %0, %1, %2;" : "=r"(r) : "f"(hi), "f"(lo)); return r; }
__device__ __forceinline__ float bf_lo(uint32_t v) { return __uint_as_float(v << 16); }
__device__ __forceinline__ float bf_hi(uint32_t v) { return __uint_as_float(v & 0xFFFF0000u); }
__device__ __forceinline__ float silu_f(float x) {
    float e, r;
    asm("ex2.approx.ftz.f32 %0, %1;" : "=f"(e) : "f"(x * -1.4426950408889634f));
    asm("rcp.approx.ftz.f32 %0, %1;" : "=f"(r) : "f"(1.0f + e));
    return x * r;
}
__device__ __forceinline__ uint32_t silu_bf2(uint32_t v) { return pack_bf2(silu_f(bf_lo(v)), silu_f(bf_hi(v))); }

__device__ __forceinline__ int kv_chunk(int q) { return q ^ ((q >> 3) & 1); }

#define H3_STAMP(i) do {} while (0)
#define H3_GSTAMP(i) do {} while (0)

template <int CH>
__device__ __forceinline__ void swiglu_chunk(const uint32_t (&pg)[32], const uint32_t (&pu)[32], uint32_t addr) {
    uint32_t h[4];
#pragma unroll
    for (int i = 0; i < 4; i++) h[i] = bf2_mul(silu_bf2(pg[4 * CH + i]), pu[4 * CH + i]);
    stsm_x4(addr, h[0], h[1], h[2], h[3]);
}
__device__ __forceinline__ void swiglu_chunk_dyn(int ci, const uint32_t (&pg)[32], const uint32_t (&pu)[32], uint32_t addr) {
    switch (ci) {
        case 0: swiglu_chunk<0>(pg, pu, addr); break;
        case 1: swiglu_chunk<1>(pg, pu, addr); break;
        case 2: swiglu_chunk<2>(pg, pu, addr); break;
        case 3: swiglu_chunk<3>(pg, pu, addr); break;
        case 4: swiglu_chunk<4>(pg, pu, addr); break;
        case 5: swiglu_chunk<5>(pg, pu, addr); break;
        case 6: swiglu_chunk<6>(pg, pu, addr); break;
        default: swiglu_chunk<7>(pg, pu, addr); break;
    }
}
__device__ __forceinline__ void wgmma_128_lo(float (&d)[128], uint64_t a, uint64_t b, int scale_d) {
    asm volatile("{\n.reg .pred p;\nsetp.ne.b32 p, %66, 0;\n"
    "wgmma.mma_async.sync.aligned.m64n128k16.f32.bf16.bf16 "
    "{%0,%1,%2,%3,%4,%5,%6,%7,%8,%9,%10,%11,%12,%13,%14,%15,"
    "%16,%17,%18,%19,%20,%21,%22,%23,%24,%25,%26,%27,%28,%29,%30,%31,"
    "%32,%33,%34,%35,%36,%37,%38,%39,%40,%41,%42,%43,%44,%45,%46,%47,"
    "%48,%49,%50,%51,%52,%53,%54,%55,%56,%57,%58,%59,%60,%61,%62,%63},"
    "%64, %65, p, 1, 1, 0, 1;\n}\n"
    : H3_R64(0)
    : "l"(a), "l"(b), "r"(scale_d));
}

template <int JP>
__device__ __forceinline__ void conv_steps(float (&acc)[16][4], const uint32_t (&b)[16][2], uint32_t ha0, uint32_t ha1, uint32_t ha2, uint32_t mk0, uint32_t mk2) {
    uint32_t g0 = lds32_o<-JP * 256>(ha0), g1 = lds32_o<-JP * 256>(ha1), g2 = lds32_o<-JP * 256>(ha2);
    if (JP == 0) { g0 &= mk0; g2 &= mk2; }
#pragma unroll
    for (int Q = JP; Q < 16; Q++) mma_16816(acc[Q], g0, g1, g2, g0, b[Q - JP][0], b[Q - JP][1]);
    if constexpr (JP < 15) conv_steps<JP + 1>(acc, b, ha0, ha1, ha2, mk0, mk2);
}

__global__ void __launch_bounds__(384, 1) h3_kernel(const __grid_constant__ Params p) {
    extern __shared__ uint8_t smem_raw[];
    const uint32_t sb = (smem_u32(smem_raw) + 1023) & ~1023u;
    const uint32_t bars = sb + OFF_BAR;
    const int tid = threadIdx.x;
    const int wg = tid >> 7;
    const int lane = tid & 31;
    const int cta = blockIdx.x;
    const int pair = cta >> 1;
    const uint32_t rank = cta & 1;

    if (tid == 0) {
        H3_STAMP(0); H3_GSTAMP(30);
#pragma unroll 1
        for (int s = 0; s < 4; s++) { mbar_init(bars + BAR_FULLA + 8 * s, 1); mbar_init(bars + BAR_EMPTYA + 8 * s, 2); mbar_init(bars + BAR_FINALA + 8 * s, 4); }
#pragma unroll 1
        for (int s = 0; s < 6; s++) { mbar_init(bars + BAR_FULLB + 8 * s, 1); mbar_init(bars + BAR_EMPTYB + 8 * s, 4); }
        mbar_init(bars + BAR_Q, 1);
        mbar_init(bars + BAR_STGFULL, 4); mbar_init(bars + BAR_STGFULL + 8, 4);
        mbar_init(bars + BAR_STGEMPTY, 1); mbar_init(bars + BAR_STGEMPTY + 8, 1);
        mbar_init(bars + BAR_YFULL, 8);
        sts128(bars + OFF_ZERO, 0, 0, 0, 0);
        asm volatile("fence.mbarrier_init.release.cluster;" ::: "memory");
        mbar_expect_tx(bars + BAR_Q, 32768);
        bulk_g2s(sb + OFF_STG, p.q + (size_t)cta * 16 * D, 32768, bars + BAR_Q);
    }
    __syncthreads();
    cluster_arrive();

    const int m1 = 2 * (pair >> 3) + (int)rank;
    const int nb1 = pair & 7;
    const int m2 = pair >> 2;
    const int nh = 24 + (pair & 3);
    const int n2 = (pair & 3) * 256 + (int)rank * 128;

    if (wg == 0) {
        asm volatile("setmaxnreg.dec.sync.aligned.u32 56;\n");
        const int warp = tid >> 5;
        if (warp == 0) {
            if (lane == 0) {
#pragma unroll 1
                for (int g = 0; g < 48; g++) {
                    const int st = g & 3, kb = g & 15;
                    const uint32_t full = bars + BAR_FULLA + 8 * st;
                    const uint32_t a = sb + st * A_STAGE;
                    if (g >= 4) mbar_wait(bars + BAR_EMPTYA + 8 * st, ((g >> 2) - 1) & 1);
                    mbar_expect_tx(full, A_STAGE);
                    const int ng = (8 * (g >> 4) + nb1) * 2;
                    tma_3d(a + 16384, &p.tmWg2, 0, kb * 64, ng, full);
                    tma_3d(a + 32768, &p.tmWu2, 0, kb * 64, ng, full);
                    int j = g;
                    if (g < 3) continue;
                    if (g == 3) { flag_wait(p.flags + (FL_XN + m1) * FLAG_STRIDE, 64); H3_STAMP(1); j = 0; }
#pragma unroll 1
                    for (; j <= g; j++) tma_2d(sb + (j & 3) * A_STAGE, &p.tmXn128, (j & 15) * 64, m1 * 128, bars + BAR_FULLA + 8 * (j & 3));
                }
                cluster_wait();
                flag_wait(p.flags + (FL_XN + m2) * FLAG_STRIDE, 64);
                int st = 0; uint32_t ph = 1;
#pragma unroll 1
                for (int e = 0; e <= E_EPI_Y; e++) {
                    const uint32_t full = bars + BAR_FULLB + 8 * st;
                    const uint32_t a = sb + st * B_STAGE;
                    if (e < 6) {
                        if (e != 2 && e != 5) mbar_wait(bars + BAR_FINALA + 8 * (e - (e >= 3)), 0);
                    } else {
                        mbar_wait(bars + BAR_EMPTYB + 8 * st, ph);
                    }
                    if (e >= E_CONV_A && e < E_G2) {
                        mbar_arrive(full);
                    } else {
                        if (e == E_CONV_U) flag_wait(p.flags + FL_KV * FLAG_STRIDE, 2 * NCTA);
                        if (e == E_G2) { flag_wait(p.flags + (FL_H + m2) * FLAG_STRIDE, 32); H3_STAMP(2); }
                        if (e == E_EPI_Y) flag_wait(p.flags + (FL_Y + (n2 >> 7)) * FLAG_STRIDE, 16);
                        mbar_expect_tx(full, B_STAGE);
                        if (e < E_CONV_H) {
                            tma_2d_mc(a + rank * 8192, &p.tmXn64, e * 64, m2 * 128 + rank * 64, full);
                            tma_3d(a + 16384, &p.tmWg1, 0, e * 64, nh * 2 + rank, full);
                            tma_3d(a + 24576, &p.tmWu1, 0, e * 64, nh * 2 + rank, full);
                        } else if (e < E_CONV_A) {
                            bulk_g2s(a, ((e == E_CONV_H) ? p.ssm_k : p.kvT) + (size_t)cta * 8 * S, 32768, full);
                        } else if (e < E_EPI_X) {
                            const int kb = e - E_G2;
                            tma_2d_mc(a + rank * 8192, &p.tmH64, kb * 64, m2 * 128 + rank * 64, full);
                            tma_3d(a + 16384, &p.tmWd, 0, kb * 64, n2 >> 6, full);
                        } else {
                            const CUtensorMap* tm = (e == E_EPI_X) ? &p.tmX128 : (e == E_EPI_XN) ? &p.tmXn128 : &p.tmY2T;
                            const int c0 = (e == E_EPI_Y) ? m2 * 128 : n2, c1 = (e == E_EPI_Y) ? n2 : m2 * 128;
                            tma_2d(a, tm, c0, c1, full);
                            tma_2d(a + 16384, tm, c0 + 64, c1, full);
                        }
                    }
                    if (++st == 6) { st = 0; ph ^= 1; }
                }
                unsigned old;
                asm volatile("atom.acq_rel.gpu.global.add.u32 %0, [%1], 1;" : "=r"(old) : "l"(p.flags + FL_DONE * FLAG_STRIDE) : "memory");
                if (old == NCTA - 1) {
#pragma unroll 1
                    for (int i = 0; i < FL_COUNT; i++) p.flags[i * FLAG_STRIDE] = 0;
                }
            } else {
                cluster_wait();
            }
        } else if (warp == 1) {
            cluster_wait();
            if (lane == 0) {
#pragma unroll 1
                for (int job = 0; job < 4; job++) {
                    const int mm = (job < 3) ? m1 : m2;
                    const int col = (job < 3) ? (8 * job + nb1) * 128 : nh * 128 + (int)rank * 64;
#pragma unroll 1
                    for (int w2 = 0; w2 < 2; w2++) {
                        mbar_wait(bars + BAR_STGFULL + 8 * w2, job & 1);
                        tma_store_2d(&p.tmH64, sb + OFF_STG + w2 * 16384, col, mm * 128 + w2 * 64);
                        if (job < 3) tma_store_2d(&p.tmH64, sb + OFF_STG + w2 * 16384 + 8192, col + 64, mm * 128 + w2 * 64);
                        bulk_commit();
                    }
                    bulk_wait_read();
                    mbar_arrive(bars + BAR_STGEMPTY); mbar_arrive(bars + BAR_STGEMPTY + 8);
                    bulk_wait_all();
                    asm volatile("fence.proxy.async;" ::: "memory");
                    flag_add(p.flags + (FL_H + mm) * FLAG_STRIDE);
                }
                mbar_wait(bars + BAR_YFULL, 0);
                bulk_s2g(p.y2T + (size_t)cta * 8 * S, sb + OFF_STG, 32768);
                bulk_commit();
                bulk_wait_all();
                asm volatile("fence.proxy.async;" ::: "memory");
                flag_add(p.flags + (FL_Y + (cta >> 4)) * FLAG_STRIDE);
            }
        } else {
            cluster_wait();
            mbar_wait(bars + BAR_Q, 0);
            const int t0 = cta * 16;
            const uint32_t* k32 = reinterpret_cast<const uint32_t*>(p.k);
            const uint32_t* v32 = reinterpret_cast<const uint32_t*>(p.v);
#pragma unroll 1
            for (int task = warp - 2; task < 32; task += 2) {
                const int cg = task >> 1;
                const int tb = t0 + (task & 1) * 8;
                const int c2 = cg * 32 + lane;
                const uint4 sw = __ldg(reinterpret_cast<const uint4*>(p.shift_k) + c2);
                uint32_t kk[11], vv[8];
#pragma unroll
                for (int i = 0; i < 11; i++) { int t = tb - 3 + i; kk[i] = (t >= 0) ? __ldg(k32 + (size_t)t * (D / 2) + c2) : 0u; }
#pragma unroll
                for (int i = 0; i < 8; i++) vv[i] = __ldg(v32 + (size_t)(tb + i) * (D / 2) + c2);
                const uint32_t w0 = __byte_perm(sw.x, sw.z, 0x5410), w1 = __byte_perm(sw.x, sw.z, 0x7632);
                const uint32_t w2 = __byte_perm(sw.y, sw.w, 0x5410), w3 = __byte_perm(sw.y, sw.w, 0x7632);
                uint32_t kv[8];
#pragma unroll
                for (int i = 0; i < 8; i++) {
                    uint32_t s = bf2_mul(kk[i], w3);
                    s = bf2_add(s, bf2_mul(kk[i + 1], w2));
                    s = bf2_add(s, bf2_mul(kk[i + 2], w1));
                    s = bf2_add(s, bf2_mul(kk[i + 3], w0));
                    kv[i] = bf2_mul(s, vv[i]);
                }
                uint4 o0, o1;
                o0.x = __byte_perm(kv[0], kv[1], 0x5410); o1.x = __byte_perm(kv[0], kv[1], 0x7632);
                o0.y = __byte_perm(kv[2], kv[3], 0x5410); o1.y = __byte_perm(kv[2], kv[3], 0x7632);
                o0.z = __byte_perm(kv[4], kv[5], 0x5410); o1.z = __byte_perm(kv[4], kv[5], 0x7632);
                o0.w = __byte_perm(kv[6], kv[7], 0x5410); o1.w = __byte_perm(kv[6], kv[7], 0x7632);
                const int q = kv_chunk(tb >> 3);
                uint4* dst = reinterpret_cast<uint4*>(p.kvT);
                dst[(size_t)(2 * c2) * (S / 8) + q] = o0;
                dst[(size_t)(2 * c2 + 1) * (S / 8) + q] = o1;
            }
            __syncwarp();
            if (lane == 0) flag_add(p.flags + FL_KV * FLAG_STRIDE);
        }
        __syncwarp();
        cluster_sync();
    } else {
        asm volatile("setmaxnreg.inc.sync.aligned.u32 224;\n");
        const int cw = wg - 1;
        const int w = (tid >> 5) & 3;
        const int wtid = tid & 127;

        {
            const int rl = (cw * 4 + w) * 2 + (lane >> 4);
            const uint32_t src = sb + OFF_STG + rl * 2048 + (lane & 15) * 16;
            if (tid == 128) H3_STAMP(15);
            mbar_wait(bars + BAR_Q, 0);
            if (tid == 128) H3_STAMP(16);
            float s = 0.f;
#pragma unroll 2
            for (int i = 0; i < 8; i++) {
                const uint4 x = lds128(src + i * 256);
                s += (bf_lo(x.x) + bf_hi(x.x)) + (bf_lo(x.y) + bf_hi(x.y));
                s += (bf_lo(x.z) + bf_hi(x.z)) + (bf_lo(x.w) + bf_hi(x.w));
            }
#pragma unroll
            for (int o = 8; o > 0; o >>= 1) s += __shfl_xor_sync(0xffffffffu, s, o);
            const float mu = s * (1.0f / D);
            float v = 0.f;
#pragma unroll 1
            for (int i = 0; i < 8; i++) {
                const uint4 x = lds128(src + i * 256);
                const uint32_t ww[4] = {x.x, x.y, x.z, x.w};
#pragma unroll
                for (int e = 0; e < 4; e++) { const float a = bf_lo(ww[e]) - mu, b = bf_hi(ww[e]) - mu; v = fmaf(a, a, v); v = fmaf(b, b, v); }
            }
#pragma unroll
            for (int o = 8; o > 0; o >>= 1) v += __shfl_xor_sync(0xffffffffu, v, o);
            if (tid == 128) H3_STAMP(17);
            const uint32_t mu2 = pack_bf2(mu, mu);
            const float vb = bf_lo(pack_bf2(v * (1.0f / D), 0.f));
            const float ve = bf_lo(pack_bf2(vb + 1e-5f, 0.f));
            const float sd = bf_lo(pack_bf2(sqrtf(ve), 0.f));
            const float inv = __frcp_rn(sd);
            uint4* dst = reinterpret_cast<uint4*>(p.xn + (size_t)(cta * 16 + rl) * D) + (lane & 15);
#pragma unroll 1
            for (int i = 0; i < 8; i++) {
                const uint4 x = lds128(src + i * 256);
                const uint32_t ww[4] = {x.x, x.y, x.z, x.w};
                uint32_t oo[4];
#pragma unroll
                for (int e = 0; e < 4; e++) { const uint32_t dd = bf2_sub(ww[e], mu2); oo[e] = pack_bf2(bf_lo(dd) * inv, bf_hi(dd) * inv); }
                dst[i * 16] = make_uint4(oo[0], oo[1], oo[2], oo[3]);
            }
            __syncwarp();
            if (tid == 128) H3_STAMP(18);
            if (lane == 0) flag_add(p.flags + (FL_XN + (cta >> 3)) * FLAG_STRIDE);
            if (tid == 128) H3_STAMP(19);
            bar_sync(3, 256);
        }
        if (tid == 128) H3_STAMP(3);
        cluster_wait();

        const uint32_t lrow = w * 16 + (lane & 7) + ((lane >> 3) & 1) * 8;
        const uint32_t lrow7 = lane & 7;
        const uint32_t lgrp = lane >> 4;
        const uint32_t stg_lane = sb + OFF_STG + cw * 16384 + lrow * 128;
        const uint64_t descA = make_desc(sb + cw * 8192, 16, 1024);
        const uint64_t descB = make_desc(sb + 16384, 8192, 1024);

        int st = 0; uint32_t ph = 0;
        {
            float acc[128];
            uint32_t pg[32], pu[32];
            int prev = 0;
#pragma unroll 1
            for (int g = 0; g < 69; g++) {
                const int kb = g & 15;
                if (g < 48) {
                    const int sa = g & 3;
                    mbar_wait(bars + BAR_FULLA + 8 * sa, (g >> 2) & 1);
                    if (g == 0 && tid == 128) H3_STAMP(4);
                    const uint64_t da = descA + sa * (A_STAGE >> 4), db = descB + sa * (A_STAGE >> 4);
                    wg_fence();
                    wgmma_256(acc, da, db, kb != 0);
#pragma unroll
                    for (int k = 1; k < 4; k++) wgmma_256(acc, da + k * 2, db + k * 128, 1);
                    wg_commit();
                } else if (g < 64) {
                    mbar_wait(bars + BAR_FULLB + 8 * st, ph);
                    const uint64_t da = descA + st * (B_STAGE >> 4), db = descB + st * (B_STAGE >> 4);
                    wg_fence();
                    wgmma_128_lo(acc, da, db, kb != 0);
#pragma unroll
                    for (int k = 1; k < 4; k++) wgmma_128_lo(acc, da + k * 2, db + k * 128, 1);
                    wg_commit();
                }
                const int nch = (g < 64) ? 8 : 4;
                if (g >= 16 && kb >= 1 && kb <= nch) {
                    if (kb == 1 && g >= 32) mbar_wait(bars + BAR_STGEMPTY + 8 * cw, (g >> 4) & 1);
                    const uint32_t grp = 2 * (kb - 1) + lgrp;
                    swiglu_chunk_dyn(kb - 1, pg, pu, stg_lane + (grp >> 3) * 8192 + (((grp & 7) ^ lrow7) << 4));
                    if (kb == nch) { fence_async_smem(); __syncwarp(); if (lane == 0) mbar_arrive(bars + BAR_STGFULL + 8 * cw); }
                }
                if (g < 64) {
                    wg_wait<1>();
                    if (kb > 0) {
                        if (g > 48) { if (wtid < 2) mbar_arrive_cta(bars + BAR_EMPTYB + 8 * prev, wtid); }
                        else if (g > 44) { if (wtid < 2) mbar_arrive_cta(bars + BAR_FINALA + 8 * (g - 45), wtid); }
                        else if (wtid == 0) mbar_arrive(bars + BAR_EMPTYA + 8 * ((g - 1) & 3));
                    }
                    if (g >= 48) { prev = st; if (++st == 6) { st = 0; ph ^= 1; } }
                    if (kb == 15) {
                        wg_wait<0>();
                        if (g == 63) {
                            if (wtid < 2) mbar_arrive_cta(bars + BAR_EMPTYB + 8 * prev, wtid);
#pragma unroll
                            for (int i = 0; i < 16; i++) { pg[i] = pack_bf2(acc[2 * i], acc[2 * i + 1]); pu[i] = pack_bf2(acc[32 + 2 * i], acc[32 + 2 * i + 1]); }
                        } else {
                            if (g == 47) { if (wtid < 2) mbar_arrive_cta(bars + BAR_FINALA + 24, wtid); }
                            else if (wtid == 0) mbar_arrive(bars + BAR_EMPTYA + 24);
#pragma unroll
                            for (int i = 0; i < 32; i++) { pg[i] = pack_bf2(acc[2 * i], acc[2 * i + 1]); pu[i] = pack_bf2(acc[64 + 2 * i], acc[64 + 2 * i + 1]); }
                        }
                        if (tid == 128) H3_STAMP(5 + (g >> 4) + (g == 63 ? 6 : 0));
                    }
                }
            }
            wg_wait<0>();
            if (tid == 128) H3_STAMP(8);
        }
        {
            const int r = lane >> 2, c = lane & 3;
            const int ch = cw * 4 + w;
            const uint32_t sH = sb + (E_CONV_H % 6) * B_STAGE + ch * 4096;
            const uint32_t sU = sb + (E_CONV_U % 6) * B_STAGE + ch * 4096;
            const uint32_t sA = sb + (E_CONV_A % 6) * B_STAGE + ch * 4096;
            const uint32_t sB = sb + (E_CONV_B % 6) * B_STAGE + ch * 4096;
            mbar_wait(bars + BAR_FULLB + 8 * (E_CONV_H % 6), (E_CONV_H / 6) & 1);
            mbar_wait(bars + BAR_FULLB + 8 * (E_CONV_A % 6), (E_CONV_A / 6) & 1);
            mbar_wait(bars + BAR_FULLB + 8 * (E_CONV_B % 6), (E_CONV_B / 6) & 1);
#pragma unroll 2
            for (int i = 0; i < 8; i++) {
                const int Q = i * 32 + lane;
                const uint4 a = lds128(sH + (255 - Q) * 16);
                uint32_t prev = 0;
                if (Q < 255) prev = lds32(sH + (254 - Q) * 16 + 12);
                sts128(sA + Q * 16, __byte_perm(a.w, 0, 0x1032), __byte_perm(a.z, 0, 0x1032), __byte_perm(a.y, 0, 0x1032), __byte_perm(a.x, 0, 0x1032));
                sts128(sB + (Q ^ 2) * 16, __byte_perm(a.w, a.z, 0x7610), __byte_perm(a.z, a.y, 0x7610), __byte_perm(a.y, a.x, 0x7610), __byte_perm(a.x, prev, 0x7610));
            }
            bar_sync(1 + cw, 128);
            if (wtid < 2) mbar_arrive_cta(bars + BAR_EMPTYB + 8 * (E_CONV_H % 6), wtid);
            mbar_wait(bars + BAR_FULLB + 8 * (E_CONV_U % 6), (E_CONV_U / 6) & 1);
            if (tid == 128) H3_STAMP(9);

            float acc[16][4];
#pragma unroll
            for (int Q = 0; Q < 16; Q++) { acc[Q][0] = acc[Q][1] = acc[Q][2] = acc[Q][3] = 0.f; }
            const bool useA = (r & 1);
            const uint32_t hbase = useA ? sA : sB;
            const int wlane = useA ? (2047 - r + 2 * c) / 2 : (2046 - r + 2 * c) / 2;
            const uint32_t xorm = useA ? 0u : 8u;
            const int y0 = r - 2 * c;
            const uint32_t mask0 = (y0 >= 0 ? 0x0000FFFFu : 0u) | (y0 >= 1 ? 0xFFFF0000u : 0u);
            const int l8 = lane & 7, lhalf = (lane >> 3) & 1, lP = lane >> 4;
#pragma unroll 1
            for (int jj = 0; jj < 8; jj++) {
                uint32_t b[16][2];
                {
                    const int p0 = 8 * lP - jj + l8;
                    const uint32_t a_rest = sU + (uint32_t)((p0 + 16) * 32) + (uint32_t)(((lhalf ^ (((p0 + 16) >> 2) & 1))) << 4);
                    const uint32_t a_first = (p0 >= 0) ? (a_rest - 512) : (bars + OFF_ZERO);
                    ldsm_x4(a_first, b[0][0], b[0][1], b[1][0], b[1][1]);
                    ldsm_x4_o<0 * 256>(a_rest, b[2][0], b[2][1], b[3][0], b[3][1]);
                    ldsm_x4_o<2 * 256>(a_rest, b[4][0], b[4][1], b[5][0], b[5][1]);
                    ldsm_x4_o<4 * 256>(a_rest, b[6][0], b[6][1], b[7][0], b[7][1]);
                    ldsm_x4_o<6 * 256>(a_rest, b[8][0], b[8][1], b[9][0], b[9][1]);
                    ldsm_x4_o<8 * 256>(a_rest, b[10][0], b[10][1], b[11][0], b[11][1]);
                    ldsm_x4_o<10 * 256>(a_rest, b[12][0], b[12][1], b[13][0], b[13][1]);
                    ldsm_x4_o<12 * 256>(a_rest, b[14][0], b[14][1], b[15][0], b[15][1]);
                }
                const int wb = wlane - 8 * jj;
                const uint32_t ha0 = hbase + (((uint32_t)wb ^ xorm) << 2);
                const uint32_t ha1 = hbase + (((uint32_t)(wb - 4) ^ xorm) << 2);
                const uint32_t ha2 = hbase + (((uint32_t)(wb + 4) ^ xorm) << 2);
                const uint32_t mk0 = (jj == 0) ? mask0 : 0xFFFFFFFFu, mk2 = (jj == 0) ? 0u : 0xFFFFFFFFu;
                conv_steps<0>(acc, b, ha0, ha1, ha2, mk0, mk2);
            }
            if (tid == 128) H3_STAMP(10);
            mbar_wait(bars + BAR_STGEMPTY + 8 * cw, 1);
            {
                const unsigned short dsc = __ldg(reinterpret_cast<const unsigned short*>(p.ssm_D) + cta * 8 + ch);
                const uint32_t d2 = (uint32_t)dsc | ((uint32_t)dsc << 16);
                const uint32_t u_l = sU + (uint32_t)((8 * lP + l8) * 32) + (uint32_t)((lhalf ^ ((l8 >> 2) & 1)) << 4);
                const uint32_t y_l = sb + OFF_STG + ch * 4096 + (uint32_t)((8 * lP + l8) * 32) + (uint32_t)(lhalf << 4);
#pragma unroll
                for (int Q = 0; Q < 16; Q += 2) {
                    uint32_t k0, k1, k2, k3;
                    ldsm_x4_t(u_l + Q * 256, k0, k1, k2, k3);
                    const uint32_t y0v = bf2_add(pack_bf2(acc[Q][0], acc[Q][1]), bf2_mul(k0, d2));
                    const uint32_t y1v = bf2_add(pack_bf2(acc[Q][2], acc[Q][3]), bf2_mul(k1, d2));
                    const uint32_t y2v = bf2_add(pack_bf2(acc[Q + 1][0], acc[Q + 1][1]), bf2_mul(k2, d2));
                    const uint32_t y3v = bf2_add(pack_bf2(acc[Q + 1][2], acc[Q + 1][3]), bf2_mul(k3, d2));
                    stsm_x4_t(y_l + Q * 256, y0v, y1v, y2v, y3v);
                }
                fence_async_smem();
                __syncwarp();
                if (lane == 0) mbar_arrive(bars + BAR_YFULL);
            }
            bar_sync(1 + cw, 128);
            if (wtid < 2) {
                mbar_arrive_cta(bars + BAR_EMPTYB + 8 * (E_CONV_U % 6), wtid);
                mbar_arrive_cta(bars + BAR_EMPTYB + 8 * (E_CONV_A % 6), wtid);
                mbar_arrive_cta(bars + BAR_EMPTYB + 8 * (E_CONV_B % 6), wtid);
            }
            if (tid == 128) H3_STAMP(11);
        }
        {
            float acc[64];
            st = E_G2 % 6; ph = (E_G2 / 6) & 1;
            int prev = 0;
#pragma unroll 1
            for (int kb = 0; kb < 56; kb++) {
                mbar_wait(bars + BAR_FULLB + 8 * st, ph);
                const uint64_t da = descA + st * (B_STAGE >> 4), db = descB + st * (B_STAGE >> 4);
                wg_fence();
                wgmma_128(acc, da, db, kb != 0);
#pragma unroll
                for (int k = 1; k < 4; k++) wgmma_128(acc, da + k * 2, db + k * 128, 1);
                wg_commit();
                wg_wait<1>();
                if (kb > 0 && wtid < 2) mbar_arrive_cta(bars + BAR_EMPTYB + 8 * prev, wtid);
                prev = st;
                if (++st == 6) { st = 0; ph ^= 1; }
            }
            wg_wait<0>();
            if (tid == 128) H3_STAMP(12);
            const uint32_t sX = sb + (E_EPI_X % 6) * B_STAGE, sXn = sb + (E_EPI_XN % 6) * B_STAGE, sY = sb + (E_EPI_Y % 6) * B_STAGE;
            mbar_wait(bars + BAR_FULLB + 8 * (E_EPI_X % 6), (E_EPI_X / 6) & 1);
            mbar_wait(bars + BAR_FULLB + 8 * (E_EPI_XN % 6), (E_EPI_XN / 6) & 1);
            mbar_wait(bars + BAR_FULLB + 8 * (E_EPI_Y % 6), (E_EPI_Y / 6) & 1);
            if (tid == 128) H3_STAMP(20);
            const uint32_t xrow = (cw * 64 + lrow) * 128;
            const uint32_t lhalf = (lane >> 3) & 1;
            const uint32_t ycol = cw * 16384 + (((2 * w + lhalf) ^ lrow7) << 4) + lrow7 * 128;
#pragma unroll 1
            for (int g2 = 0; g2 < 4; g2++) {
#pragma unroll
                for (int hh = 0; hh < 2; hh++) {
                    const uint32_t grp = g2 * 4 + hh * 2 + lgrp;
                    const uint32_t xoff = (grp >> 3) * 16384 + xrow + (((grp & 7) ^ lrow7) << 4);
                    uint32_t x0, x1, x2, x3, n0, n1, n2v, n3, y0, y1, y2, y3;
                    ldsm_x4(sX + xoff, x0, x1, x2, x3);
                    ldsm_x4(sXn + xoff, n0, n1, n2v, n3);
                    ldsm_x4_t(sY + ycol + grp * 1024, y0, y1, y2, y3);
                    const float* a = acc + hh * 8;
                    const uint32_t o0 = bf2_add(x0, bf2_mul(bf2_mul(n0, y0), silu_bf2(pack_bf2(a[0], a[1]))));
                    const uint32_t o1 = bf2_add(x1, bf2_mul(bf2_mul(n1, y1), silu_bf2(pack_bf2(a[2], a[3]))));
                    const uint32_t o2 = bf2_add(x2, bf2_mul(bf2_mul(n2v, y2), silu_bf2(pack_bf2(a[4], a[5]))));
                    const uint32_t o3 = bf2_add(x3, bf2_mul(bf2_mul(n3, y3), silu_bf2(pack_bf2(a[6], a[7]))));
                    stsm_x4(sX + xoff, o0, o1, o2, o3);
                }
#pragma unroll
                for (int i = 0; i < 48; i++) acc[i] = acc[i + 16];
            }
            if (tid == 128) H3_STAMP(21);
            fence_async_smem();
            bar_sync(1 + cw, 128);
            if (tid == 128) H3_STAMP(22);
            if (wtid == 0) {
                tma_store_2d(&p.tmOut64, sX + cw * 8192, n2, m2 * 128 + cw * 64);
                tma_store_2d(&p.tmOut64, sX + 16384 + cw * 8192, n2 + 64, m2 * 128 + cw * 64);
                bulk_commit();
                bulk_wait_all();
            }
            if (tid == 128) { H3_STAMP(13); H3_GSTAMP(31); }
        }
        cluster_sync();
    }
}

typedef CUresult (*EncodeTiledFn)(CUtensorMap*, CUtensorMapDataType, cuuint32_t, void*, const cuuint64_t*, const cuuint64_t*,
                                  const cuuint32_t*, const cuuint32_t*, CUtensorMapInterleave, CUtensorMapSwizzle,
                                  CUtensorMapL2promotion, CUtensorMapFloatOOBfill);

static void make_map(EncodeTiledFn enc, CUtensorMap* m, const void* ptr, int rank, const uint64_t* dims, const uint64_t* strides, const uint32_t* box) {
    cuuint64_t d[3], s[2];
    cuuint32_t b[3], es[3] = {1, 1, 1};
    for (int i = 0; i < rank; i++) { d[i] = dims[i]; b[i] = box[i]; }
    for (int i = 0; i + 1 < rank; i++) s[i] = strides[i];
    CUresult r = enc(m, CU_TENSOR_MAP_DATA_TYPE_BFLOAT16, rank, const_cast<void*>(ptr), d, s, b, es, CU_TENSOR_MAP_INTERLEAVE_NONE,
                     CU_TENSOR_MAP_SWIZZLE_128B, CU_TENSOR_MAP_L2_PROMOTION_L2_128B, CU_TENSOR_MAP_FLOAT_OOB_FILL_NONE);
    if (r != CUDA_SUCCESS) fprintf(stderr, "cuTensorMapEncodeTiled failed: %d\n", (int)r);
}
static void map2d(EncodeTiledFn enc, CUtensorMap* m, const void* ptr, uint64_t cols, uint64_t rows, uint32_t box_rows) {
    const uint64_t d[2] = {cols, rows}, s[1] = {cols * 2};
    const uint32_t b[2] = {64, box_rows};
    make_map(enc, m, ptr, 2, d, s, b);
}
static void map3d(EncodeTiledFn enc, CUtensorMap* m, const void* ptr, uint64_t cols, uint64_t rows, uint32_t groups) {
    const uint64_t d[3] = {64, rows, cols / 64}, s[2] = {cols * 2, 128};
    const uint32_t b[3] = {64, 64, groups};
    make_map(enc, m, ptr, 3, d, s, b);
}

static long long* g_dbg_ptr = nullptr;

}

extern "C" void kernel_launch(void* const* d_in, const int* in_sizes, int n_in, void* d_out, int out_size) {
    using namespace h3;
    (void)in_sizes; (void)n_in; (void)out_size;
    static EncodeTiledFn enc = nullptr;
    static void *xn, *kvT, *hbuf, *y2T, *flags;
    if (!enc) {
        void* fn = nullptr;
        cudaDriverEntryPointQueryResult qr;
        cudaGetDriverEntryPoint("cuTensorMapEncodeTiled", &fn, cudaEnableDefault, &qr);
        enc = (EncodeTiledFn)fn;
        cudaGetSymbolAddress(&xn, g_xn);
        cudaGetSymbolAddress(&kvT, g_kvT);
        cudaGetSymbolAddress(&hbuf, g_h);
        cudaGetSymbolAddress(&y2T, g_y2T);
        cudaGetSymbolAddress(&flags, g_flags);
        cudaFuncSetAttribute(h3_kernel, cudaFuncAttributeMaxDynamicSharedMemorySize, SMEM_BYTES);
    }
    Params p;
    const bf16* q = (const bf16*)d_in[0];
    p.q = q; p.k = (const bf16*)d_in[1]; p.v = (const bf16*)d_in[2];
    p.shift_k = (const bf16*)d_in[3]; p.ssm_k = (const bf16*)d_in[4]; p.ssm_D = (const bf16*)d_in[5];
    const bf16* wg = (const bf16*)d_in[7];
    const bf16* wu = (const bf16*)d_in[8];
    const bf16* wd = (const bf16*)d_in[9];
    p.xn = (bf16*)xn; p.kvT = (bf16*)kvT; p.y2T = (bf16*)y2T; p.flags = (unsigned*)flags;
    p.dbg = g_dbg_ptr;
    map2d(enc, &p.tmXn128, xn, D, S, 128);
    map2d(enc, &p.tmXn64, xn, D, S, 64);
    map3d(enc, &p.tmWg2, wg, F, D, 2);
    map3d(enc, &p.tmWu2, wu, F, D, 2);
    map3d(enc, &p.tmWg1, wg, F, D, 1);
    map3d(enc, &p.tmWu1, wu, F, D, 1);
    map2d(enc, &p.tmH64, hbuf, F, S, 64);
    map3d(enc, &p.tmWd, wd, D, F, 2);
    map2d(enc, &p.tmX128, q, D, S, 128);
    map2d(enc, &p.tmY2T, y2T, S, D, 128);
    map2d(enc, &p.tmOut64, d_out, D, S, 64);

    cudaLaunchConfig_t cfg = {};
    cfg.gridDim = dim3(NCTA);
    cfg.blockDim = dim3(384);
    cfg.dynamicSmemBytes = SMEM_BYTES;
    cfg.stream = cudaStreamPerThread;
    cudaLaunchAttribute at[1];
    at[0].id = cudaLaunchAttributeClusterDimension;
    at[0].val.clusterDim.x = 2; at[0].val.clusterDim.y = 1; at[0].val.clusterDim.z = 1;
    cfg.attrs = at; cfg.numAttrs = 1;
    cudaLaunchKernelEx(&cfg, h3_kernel, p);
}
```

```cpp
#include <cuda_runtime.h>
#include <cuda_bf16.h>
#include <cuda.h>
#include <stdint.h>
#include <stdio.h>

namespace h3 {

typedef __nv_bfloat16 bf16;
typedef __nv_bfloat162 bf162;

constexpr int S = 2048;
constexpr int D = 1024;
constexpr int F = 3584;
constexpr int NCTA = 128;

__device__ __align__(1024) bf16 g_xn[S * D];
__device__ __align__(1024) bf16 g_kvT[D * S];
__device__ __align__(1024) bf16 g_h[S * F];
__device__ __align__(1024) bf16 g_y2T[D * S];
__device__ __align__(1024) uint2 g_stats[S];
constexpr int FLAG_STRIDE = 32;
constexpr int FL_XN = 0, FL_H = 16, FL_Y = 32, FL_KV = 40, FL_DONE = 41, FL_H2 = 42, FL_COUNT = 58;
__device__ __align__(1024) unsigned g_flags[FL_COUNT * FLAG_STRIDE];

struct alignas(64) Params {
    CUtensorMap tmXn128;
    CUtensorMap tmXn64;
    CUtensorMap tmWg2;
    CUtensorMap tmWu2;
    CUtensorMap tmWg1;
    CUtensorMap tmWu1;
    CUtensorMap tmH64;
    CUtensorMap tmWd;
    CUtensorMap tmX128;
    CUtensorMap tmY2T;
    CUtensorMap tmOut64;
    CUtensorMap tmK;
    CUtensorMap tmV;
    CUtensorMap tmKvT;
    const bf16* q; const bf16* k; const bf16* v; const bf16* shift_k; const bf16* ssm_k; const bf16* ssm_D;
    bf16* xn; bf16* kvT; bf16* y2T; uint2* stats;
    unsigned* flags;
    long long* dbg;
};

constexpr uint32_t RING_BYTES = 196608;
constexpr uint32_t A_STAGE = 49152, B_STAGE = 32768;
constexpr uint32_t OFF_STG = RING_BYTES + 1024;
constexpr uint32_t OFF_BAR = OFF_STG + 32768;
constexpr uint32_t BAR_FULLA = 0, BAR_EMPTYA = 32, BAR_FINALA = 64, BAR_FULLB = 96, BAR_EMPTYB = 144,
                   BAR_STGFULL = 200, BAR_STGEMPTY = 208, BAR_ALTFULL = 216, BAR_REDFREE = 224, BAR_OPFULL = 232,
                   BAR_ALT2FULL = 240, OFF_STAT = 256;
constexpr uint32_t SMEM_BYTES = OFF_BAR + 512 + 1024;

constexpr int ST_H = 4, ST_U = 5, ST_C0 = 0, ST_C1 = 1, ST_ALT = 2, ST_ALT2 = 3;
constexpr uint32_t U_PITCH = 4096 + 16;

__device__ __forceinline__ uint32_t smem_u32(const void* p) { return (uint32_t)__cvta_generic_to_shared(p); }
__device__ __forceinline__ uint64_t make_desc(uint32_t addr, uint32_t lbo, uint32_t sbo) {
    uint64_t d = (uint64_t)((addr & 0x3FFFF) >> 4);
    d |= (uint64_t)((lbo & 0x3FFFF) >> 4) << 16;
    d |= (uint64_t)((sbo & 0x3FFFF) >> 4) << 32;
    d |= (uint64_t)1 << 62;
    return d;
}
__device__ __forceinline__ uint64_t make_desc_noswz(uint32_t addr, uint32_t lbo, uint32_t sbo) {
    return (uint64_t)((addr & 0x3FFFF) >> 4) | ((uint64_t)(lbo >> 4) << 16) | ((uint64_t)(sbo >> 4) << 32);
}
constexpr uint32_t WAIT_LIMIT = 1u << 27;
__device__ __forceinline__ void mbar_init(uint32_t bar, uint32_t count) { asm volatile("mbarrier.init.shared::cta.b64 [%0], %1;" :: "r"(bar), "r"(count) : "memory"); }
__device__ __forceinline__ void mbar_expect_tx(uint32_t bar, uint32_t bytes) { asm volatile("mbarrier.arrive.expect_tx.shared::cta.b64 _, [%0], %1;" :: "r"(bar), "r"(bytes) : "memory"); }
__device__ __forceinline__ void mbar_arrive(uint32_t bar) { asm volatile("mbarrier.arrive.shared::cta.b64 _, [%0];" :: "r"(bar) : "memory"); }
__device__ __forceinline__ void mbar_arrive_cta(uint32_t bar, uint32_t cta) {
    asm volatile("{\n.reg .b32 ra;\nmapa.shared::cluster.u32 ra, %0, %1;\nmbarrier.arrive.shared::cluster.b64 _, [ra];\n}" :: "r"(bar), "r"(cta) : "memory");
}
__device__ __forceinline__ uint32_t mbar_try(uint32_t bar, uint32_t parity) {
    uint32_t ok;
    asm volatile("{\n.reg .pred p;\nmbarrier.try_wait.parity.shared::cta.b64 p, [%1], %2;\nselp.u32 %0, 1, 0, p;\n}" : "=r"(ok) : "r"(bar), "r"(parity) : "memory");
    return ok;
}
__device__ __forceinline__ void mbar_wait(uint32_t bar, uint32_t parity) {
    if (!mbar_try(bar, parity)) {
        const uint32_t t0 = (uint32_t)clock();
        while (!mbar_try(bar, parity) && (uint32_t)clock() - t0 < WAIT_LIMIT) {}
    }
}
__device__ __forceinline__ void flag_wait(const unsigned* f, unsigned target) {
    const uint32_t t0 = (uint32_t)clock();
    unsigned v;
    do {
        asm volatile("ld.acquire.gpu.global.u32 %0, [%1];" : "=r"(v) : "l"(f) : "memory");
    } while (v < target && (uint32_t)clock() - t0 < WAIT_LIMIT);
}
__device__ __forceinline__ void flag_add_after_bulk(unsigned* f) {
    asm volatile("red.relaxed.gpu.global.add.u32 [%0], 1;" :: "l"(f) : "memory");
}
__device__ __forceinline__ void flag_add(unsigned* f) {
    asm volatile("red.release.gpu.global.add.u32 [%0], 1;" :: "l"(f) : "memory");
}
__device__ __forceinline__ void cluster_arrive() { asm volatile("barrier.cluster.arrive.relaxed;" ::: "memory"); }
__device__ __forceinline__ void cluster_wait() { asm volatile("barrier.cluster.wait.acquire;" ::: "memory"); }
__device__ __forceinline__ void tma_2d(uint32_t dst, const CUtensorMap* m, int c0, int c1, uint32_t bar) {
    asm volatile("cp.async.bulk.tensor.2d.shared::cluster.global.mbarrier::complete_tx::bytes [%0], [%1, {%3, %4}], [%2];"
        :: "r"(dst), "l"(m), "r"(bar), "r"(c0), "r"(c1) : "memory");
}
__device__ __forceinline__ void tma_2d_mc(uint32_t dst, const CUtensorMap* m, int c0, int c1, uint32_t bar) {
    asm volatile("cp.async.bulk.tensor.2d.shared::cluster.global.mbarrier::complete_tx::bytes.multicast::cluster [%0], [%1, {%3, %4}], [%2], %5;"
        :: "r"(dst), "l"(m), "r"(bar), "r"(c0), "r"(c1), "h"((uint16_t)3) : "memory");
}
__device__ __forceinline__ void tma_3d(uint32_t dst, const CUtensorMap* m, int c0, int c1, int c2, uint32_t bar) {
    asm volatile("cp.async.bulk.tensor.3d.shared::cluster.global.mbarrier::complete_tx::bytes [%0], [%1, {%3, %4, %5}], [%2];"
        :: "r"(dst), "l"(m), "r"(bar), "r"(c0), "r"(c1), "r"(c2) : "memory");
}
__device__ __forceinline__ uint64_t policy_evict_first() {
    uint64_t pol; asm volatile("createpolicy.fractional.L2::evict_first.b64 %0, 1.0;" : "=l"(pol)); return pol;
}
__device__ __forceinline__ void tma_3d_h(uint32_t dst, const CUtensorMap* m, int c0, int c1, int c2, uint32_t bar, uint64_t pol) {
    asm volatile("cp.async.bulk.tensor.3d.shared::cluster.global.mbarrier::complete_tx::bytes.L2::cache_hint [%0], [%1, {%3, %4, %5}], [%2], %6;"
        :: "r"(dst), "l"(m), "r"(bar), "r"(c0), "r"(c1), "r"(c2), "l"(pol) : "memory");
}
__device__ __forceinline__ void tma_2d_h(uint32_t dst, const CUtensorMap* m, int c0, int c1, uint32_t bar, uint64_t pol) {
    asm volatile("cp.async.bulk.tensor.2d.shared::cluster.global.mbarrier::complete_tx::bytes.L2::cache_hint [%0], [%1, {%3, %4}], [%2], %5;"
        :: "r"(dst), "l"(m), "r"(bar), "r"(c0), "r"(c1), "l"(pol) : "memory");
}
__device__ __forceinline__ void pf_3d_h(const CUtensorMap* m, int c0, int c1, int c2, uint64_t pol) {
    asm volatile("cp.async.bulk.prefetch.tensor.3d.L2.global.tile.L2::cache_hint [%0, {%1, %2, %3}], %4;" :: "l"(m), "r"(c0), "r"(c1), "r"(c2), "l"(pol) : "memory");
}
__device__ __forceinline__ void pf_bulk_h(const void* src, uint32_t bytes, uint64_t pol) {
    asm volatile("cp.async.bulk.prefetch.L2.global.L2::cache_hint [%0], %1, %2;" :: "l"(src), "r"(bytes), "l"(pol) : "memory");
}
__device__ __forceinline__ void bulk_g2s_h(uint32_t dst, const void* src, uint32_t bytes, uint32_t bar, uint64_t pol) {
    asm volatile("cp.async.bulk.shared::cluster.global.mbarrier::complete_tx::bytes.L2::cache_hint [%0], [%1], %2, [%3], %4;"
        :: "r"(dst), "l"(src), "r"(bytes), "r"(bar), "l"(pol) : "memory");
}
__device__ __forceinline__ void bulk_g2s(uint32_t dst, const void* src, uint32_t bytes, uint32_t bar) {
    asm volatile("cp.async.bulk.shared::cluster.global.mbarrier::complete_tx::bytes [%0], [%1], %2, [%3];"
        :: "r"(dst), "l"(src), "r"(bytes), "r"(bar) : "memory");
}
__device__ __forceinline__ void bulk_s2g(void* dst, uint32_t src, uint32_t bytes) {
    asm volatile("cp.async.bulk.global.shared::cta.bulk_group [%0], [%1], %2;" :: "l"(dst), "r"(src), "r"(bytes) : "memory");
}
__device__ __forceinline__ void tma_store_2d(const CUtensorMap* m, uint32_t src, int c0, int c1) {
    asm volatile("cp.async.bulk.tensor.2d.global.shared::cta.bulk_group [%0, {%2, %3}], [%1];"
        :: "l"(m), "r"(src), "r"(c0), "r"(c1) : "memory");
}
__device__ __forceinline__ void pf_3d(const CUtensorMap* m, int c0, int c1, int c2) {
    asm volatile("cp.async.bulk.prefetch.tensor.3d.L2.global.tile [%0, {%1, %2, %3}];" :: "l"(m), "r"(c0), "r"(c1), "r"(c2) : "memory");
}
__device__ __forceinline__ void pf_2d(const CUtensorMap* m, int c0, int c1) {
    asm volatile("cp.async.bulk.prefetch.tensor.2d.L2.global.tile [%0, {%1, %2}];" :: "l"(m), "r"(c0), "r"(c1) : "memory");
}
__device__ __forceinline__ void pf_bulk(const void* src, uint32_t bytes) {
    asm volatile("cp.async.bulk.prefetch.L2.global [%0], %1;" :: "l"(src), "r"(bytes) : "memory");
}
__device__ __forceinline__ void bulk_commit() { asm volatile("cp.async.bulk.commit_group;" ::: "memory"); }
__device__ __forceinline__ void bulk_wait_read() { asm volatile("cp.async.bulk.wait_group.read 0;" ::: "memory"); }
__device__ __forceinline__ void bulk_wait_all() { asm volatile("cp.async.bulk.wait_group 0;" ::: "memory"); }
__device__ __forceinline__ void fence_async_smem() { asm volatile("fence.proxy.async.shared::cta;" ::: "memory"); }
__device__ __forceinline__ void prefetch_tmap(const CUtensorMap* m) { asm volatile("prefetch.tensormap [%0];" :: "l"(m) : "memory"); }
__device__ __forceinline__ void bar_sync(int id, int n) { asm volatile("bar.sync %0, %1;" :: "r"(id), "r"(n) : "memory"); }
__device__ __forceinline__ void bar_arrive(int id, int n) { asm volatile("bar.arrive %0, %1;" :: "r"(id), "r"(n) : "memory"); }
__device__ __forceinline__ void cluster_sync() {
    asm volatile("barrier.cluster.arrive.release.aligned;" ::: "memory");
    asm volatile("barrier.cluster.wait.acquire.aligned;" ::: "memory");
}
__device__ __forceinline__ void wg_fence() { asm volatile("wgmma.fence.sync.aligned;" ::: "memory"); }
__device__ __forceinline__ void wg_commit() { asm volatile("wgmma.commit_group.sync.aligned;" ::: "memory"); }
template <int N> __device__ __forceinline__ void wg_wait() { asm volatile("wgmma.wait_group.sync.aligned %0;" :: "n"(N) : "memory"); }

#define H3_R4(b)  "+f"(d[b+0]), "+f"(d[b+1]), "+f"(d[b+2]), "+f"(d[b+3])
#define H3_R8(b)  H3_R4(b), H3_R4(b+4)
#define H3_R16(b) H3_R8(b), H3_R8(b+8)
#define H3_R32(b) H3_R16(b), H3_R16(b+16)
#define H3_R64(b) H3_R32(b), H3_R32(b+32)

__device__ __forceinline__ void wgmma_256(float (&d)[128], uint64_t a, uint64_t b, int scale_d) {
    asm volatile("{\n.reg .pred p;\nsetp.ne.b32 p, %130, 0;\n"
    "wgmma.mma_async.sync.aligned.m64n256k16.f32.bf16.bf16 "
    "{%0,%1,%2,%3,%4,%5,%6,%7,%8,%9,%10,%11,%12,%13,%14,%15,"
    "%16,%17,%18,%19,%20,%21,%22,%23,%24,%25,%26,%27,%28,%29,%30,%31,"
    "%32,%33,%34,%35,%36,%37,%38,%39,%40,%41,%42,%43,%44,%45,%46,%47,"
    "%48,%49,%50,%51,%52,%53,%54,%55,%56,%57,%58,%59,%60,%61,%62,%63,"
    "%64,%65,%66,%67,%68,%69,%70,%71,%72,%73,%74,%75,%76,%77,%78,%79,"
    "%80,%81,%82,%83,%84,%85,%86,%87,%88,%89,%90,%91,%92,%93,%94,%95,"
    "%96,%97,%98,%99,%100,%101,%102,%103,%104,%105,%106,%107,%108,%109,%110,%111,"
    "%112,%113,%114,%115,%116,%117,%118,%119,%120,%121,%122,%123,%124,%125,%126,%127},"
    "%128, %129, p, 1, 1, 0, 1;\n}\n"
    : H3_R64(0), H3_R64(64)
    : "l"(a), "l"(b), "r"(scale_d));
}
__device__ __forceinline__ void wgmma_128(float (&d)[64], uint64_t a, uint64_t b, int scale_d) {
    asm volatile("{\n.reg .pred p;\nsetp.ne.b32 p, %66, 0;\n"
    "wgmma.mma_async.sync.aligned.m64n128k16.f32.bf16.bf16 "
    "{%0,%1,%2,%3,%4,%5,%6,%7,%8,%9,%10,%11,%12,%13,%14,%15,"
    "%16,%17,%18,%19,%20,%21,%22,%23,%24,%25,%26,%27,%28,%29,%30,%31,"
    "%32,%33,%34,%35,%36,%37,%38,%39,%40,%41,%42,%43,%44,%45,%46,%47,"
    "%48,%49,%50,%51,%52,%53,%54,%55,%56,%57,%58,%59,%60,%61,%62,%63},"
    "%64, %65, p, 1, 1, 0, 1;\n}\n"
    : H3_R64(0)
    : "l"(a), "l"(b), "r"(scale_d));
}
__device__ __forceinline__ void ldsm_x4(uint32_t addr, uint32_t& r0, uint32_t& r1, uint32_t& r2, uint32_t& r3) {
    asm volatile("ldmatrix.sync.aligned.m8n8.x4.shared.b16 {%0,%1,%2,%3}, [%4];" : "=r"(r0), "=r"(r1), "=r"(r2), "=r"(r3) : "r"(addr) : "memory");
}
__device__ __forceinline__ void ldsm_x4_t(uint32_t addr, uint32_t& r0, uint32_t& r1, uint32_t& r2, uint32_t& r3) {
    asm volatile("ldmatrix.sync.aligned.m8n8.x4.trans.shared.b16 {%0,%1,%2,%3}, [%4];" : "=r"(r0), "=r"(r1), "=r"(r2), "=r"(r3) : "r"(addr) : "memory");
}
__device__ __forceinline__ void stsm_x4(uint32_t addr, uint32_t r0, uint32_t r1, uint32_t r2, uint32_t r3) {
    asm volatile("stmatrix.sync.aligned.m8n8.x4.shared.b16 [%0], {%1,%2,%3,%4};" :: "r"(addr), "r"(r0), "r"(r1), "r"(r2), "r"(r3) : "memory");
}
__device__ __forceinline__ void stsm_x4_t(uint32_t addr, uint32_t r0, uint32_t r1, uint32_t r2, uint32_t r3) {
    asm volatile("stmatrix.sync.aligned.m8n8.x4.trans.shared.b16 [%0], {%1,%2,%3,%4};" :: "r"(addr), "r"(r0), "r"(r1), "r"(r2), "r"(r3) : "memory");
}
template <int OFF> __device__ __forceinline__ uint32_t lds32_o(uint32_t addr) { uint32_t v; asm volatile("ld.shared.b32 %0, [%1+%2];" : "=r"(v) : "r"(addr), "n"(OFF) : "memory"); return v; }
template <int OFF> __device__ __forceinline__ float2 lds64f_o(uint32_t addr) { float2 v; asm volatile("ld.shared.v2.f32 {%0,%1}, [%2+%3];" : "=f"(v.x), "=f"(v.y) : "r"(addr), "n"(OFF) : "memory"); return v; }
template <int OFF> __device__ __forceinline__ void sts64f_o(uint32_t addr, float a, float b) { asm volatile("st.shared.v2.f32 [%0+%1], {%2,%3};" :: "r"(addr), "n"(OFF), "f"(a), "f"(b) : "memory"); }
__device__ __forceinline__ uint32_t lds32(uint32_t addr) { uint32_t v; asm volatile("ld.shared.b32 %0, [%1];" : "=r"(v) : "r"(addr) : "memory"); return v; }
__device__ __forceinline__ uint2 lds64(uint32_t addr) { uint2 v; asm volatile("ld.shared.v2.b32 {%0,%1}, [%2];" : "=r"(v.x), "=r"(v.y) : "r"(addr) : "memory"); return v; }
__device__ __forceinline__ uint4 lds128(uint32_t addr) { uint4 v; asm volatile("ld.shared.v4.b32 {%0,%1,%2,%3}, [%4];" : "=r"(v.x), "=r"(v.y), "=r"(v.z), "=r"(v.w) : "r"(addr) : "memory"); return v; }
__device__ __forceinline__ void sts128(uint32_t addr, uint32_t a, uint32_t b, uint32_t c, uint32_t d) { asm volatile("st.shared.v4.b32 [%0], {%1,%2,%3,%4};" :: "r"(addr), "r"(a), "r"(b), "r"(c), "r"(d) : "memory"); }

__device__ __forceinline__ uint32_t bf2_mul(uint32_t a, uint32_t b) { uint32_t r; asm("mul.rn.bf16x2 %0, %1, %2;" : "=r"(r) : "r"(a), "r"(b)); return r; }
__device__ __forceinline__ uint32_t bf2_add(uint32_t a, uint32_t b) { uint32_t r; asm("add.rn.bf16x2 %0, %1, %2;" : "=r"(r) : "r"(a), "r"(b)); return r; }
__device__ __forceinline__ uint32_t bf2_sub(uint32_t a, uint32_t b) { uint32_t r; asm("sub.rn.bf16x2 %0, %1, %2;" : "=r"(r) : "r"(a), "r"(b)); return r; }
__device__ __forceinline__ uint32_t pack_bf2(float lo, float hi) { uint32_t r; asm("cvt.rn.bf16x2.f32 %0, %1, %2;" : "=r"(r) : "f"(hi), "f"(lo)); return r; }
__device__ __forceinline__ float bf_lo(uint32_t v) { return __uint_as_float(v << 16); }
__device__ __forceinline__ float bf_hi(uint32_t v) { return __uint_as_float(v & 0xFFFF0000u); }
__device__ __forceinline__ float silu_f(float x) {
    float e, r;
    asm("ex2.approx.ftz.f32 %0, %1;" : "=f"(e) : "f"(x * -1.4426950408889634f));
    asm("rcp.approx.ftz.f32 %0, %1;" : "=f"(r) : "f"(1.0f + e));
    return x * r;
}
__device__ __forceinline__ uint32_t silu_bf2(uint32_t v) { return pack_bf2(silu_f(bf_lo(v)), silu_f(bf_hi(v))); }

#define H3_TR(ph, i) do {} while (0)
#define H3_STAMP(i) do {} while (0)
#define H3_GSTAMP(i) do {} while (0)

template <int I>
__device__ __forceinline__ void stage_piece(const uint32_t (&pg)[32], const uint32_t (&pu)[32], uint32_t stg_lane, uint32_t lrow7, uint32_t lgrp) {
    const uint32_t addr = stg_lane + (((2 * (I & 3) + lgrp) ^ lrow7) << 4);
    stsm_x4(addr, pg[4 * I], pg[4 * I + 1], pg[4 * I + 2], pg[4 * I + 3]);
    stsm_x4(addr + 8192, pu[4 * I], pu[4 * I + 1], pu[4 * I + 2], pu[4 * I + 3]);
}
__device__ __forceinline__ void stage_piece_dyn(int i, const uint32_t (&pg)[32], const uint32_t (&pu)[32], uint32_t stg_lane, uint32_t lrow7, uint32_t lgrp) {
    switch (i) {
        case 0: stage_piece<0>(pg, pu, stg_lane, lrow7, lgrp); break;
        case 1: stage_piece<1>(pg, pu, stg_lane, lrow7, lgrp); break;
        case 2: stage_piece<2>(pg, pu, stg_lane, lrow7, lgrp); break;
        case 3: stage_piece<3>(pg, pu, stg_lane, lrow7, lgrp); break;
        case 4: stage_piece<4>(pg, pu, stg_lane, lrow7, lgrp); break;
        case 5: stage_piece<5>(pg, pu, stg_lane, lrow7, lgrp); break;
        case 6: stage_piece<6>(pg, pu, stg_lane, lrow7, lgrp); break;
        default: stage_piece<7>(pg, pu, stg_lane, lrow7, lgrp); break;
    }
}
__device__ __forceinline__ void wgmma_128_lo(float (&d)[128], uint64_t a, uint64_t b, int scale_d) {
    asm volatile("{\n.reg .pred p;\nsetp.ne.b32 p, %66, 0;\n"
    "wgmma.mma_async.sync.aligned.m64n128k16.f32.bf16.bf16 "
    "{%0,%1,%2,%3,%4,%5,%6,%7,%8,%9,%10,%11,%12,%13,%14,%15,"
    "%16,%17,%18,%19,%20,%21,%22,%23,%24,%25,%26,%27,%28,%29,%30,%31,"
    "%32,%33,%34,%35,%36,%37,%38,%39,%40,%41,%42,%43,%44,%45,%46,%47,"
    "%48,%49,%50,%51,%52,%53,%54,%55,%56,%57,%58,%59,%60,%61,%62,%63},"
    "%64, %65, p, 1, 1, 0, 1;\n}\n"
    : H3_R64(0)
    : "l"(a), "l"(b), "r"(scale_d));
}

template <int N> __device__ __forceinline__ void wgmma_rs(float (&d)[128], const uint32_t (&a)[4], uint64_t b, int scale_d);
template <> __device__ __forceinline__ void wgmma_rs<16>(float (&d)[128], const uint32_t (&a)[4], uint64_t b, int scale_d) {
    asm volatile("{\n.reg .pred p;\nsetp.ne.b32 p, %13, 0;\nwgmma.mma_async.sync.aligned.m64n16k16.f32.bf16.bf16 {%0,%1,%2,%3,%4,%5,%6,%7}, {%8,%9,%10,%11}, %12, p, 1, 1, 0;\n}\n"
        : "+f"(d[0]), "+f"(d[1]), "+f"(d[2]), "+f"(d[3]), "+f"(d[4]), "+f"(d[5]), "+f"(d[6]), "+f"(d[7])
        : "r"(a[0]), "r"(a[1]), "r"(a[2]), "r"(a[3]), "l"(b), "r"(scale_d));
}
template <> __device__ __forceinline__ void wgmma_rs<32>(float (&d)[128], const uint32_t (&a)[4], uint64_t b, int scale_d) {
    asm volatile("{\n.reg .pred p;\nsetp.ne.b32 p, %21, 0;\nwgmma.mma_async.sync.aligned.m64n32k16.f32.bf16.bf16 {%0,%1,%2,%3,%4,%5,%6,%7,%8,%9,%10,%11,%12,%13,%14,%15}, {%16,%17,%18,%19}, %20, p, 1, 1, 0;\n}\n"
        : "+f"(d[0]), "+f"(d[1]), "+f"(d[2]), "+f"(d[3]), "+f"(d[4]), "+f"(d[5]), "+f"(d[6]), "+f"(d[7]), "+f"(d[8]), "+f"(d[9]), "+f"(d[10]), "+f"(d[11]), "+f"(d[12]), "+f"(d[13]), "+f"(d[14]), "+f"(d[15])
        : "r"(a[0]), "r"(a[1]), "r"(a[2]), "r"(a[3]), "l"(b), "r"(scale_d));
}
template <> __device__ __forceinline__ void wgmma_rs<48>(float (&d)[128], const uint32_t (&a)[4], uint64_t b, int scale_d) {
    asm volatile("{\n.reg .pred p;\nsetp.ne.b32 p, %29, 0;\nwgmma.mma_async.sync.aligned.m64n48k16.f32.bf16.bf16 {%0,%1,%2,%3,%4,%5,%6,%7,%8,%9,%10,%11,%12,%13,%14,%15,%16,%17,%18,%19,%20,%21,%22,%23}, {%24,%25,%26,%27}, %28, p, 1, 1, 0;\n}\n"
        : "+f"(d[0]), "+f"(d[1]), "+f"(d[2]), "+f"(d[3]), "+f"(d[4]), "+f"(d[5]), "+f"(d[6]), "+f"(d[7]), "+f"(d[8]), "+f"(d[9]), "+f"(d[10]), "+f"(d[11]), "+f"(d[12]), "+f"(d[13]), "+f"(d[14]), "+f"(d[15]), "+f"(d[16]), "+f"(d[17]), "+f"(d[18]), "+f"(d[19]), "+f"(d[20]), "+f"(d[21]), "+f"(d[22]), "+f"(d[23])
        : "r"(a[0]), "r"(a[1]), "r"(a[2]), "r"(a[3]), "l"(b), "r"(scale_d));
}
template <> __device__ __forceinline__ void wgmma_rs<64>(float (&d)[128], const uint32_t (&a)[4], uint64_t b, int scale_d) {
    asm volatile("{\n.reg .pred p;\nsetp.ne.b32 p, %37, 0;\nwgmma.mma_async.sync.aligned.m64n64k16.f32.bf16.bf16 {%0,%1,%2,%3,%4,%5,%6,%7,%8,%9,%10,%11,%12,%13,%14,%15,%16,%17,%18,%19,%20,%21,%22,%23,%24,%25,%26,%27,%28,%29,%30,%31}, {%32,%33,%34,%35}, %36, p, 1, 1, 0;\n}\n"
        : "+f"(d[0]), "+f"(d[1]), "+f"(d[2]), "+f"(d[3]), "+f"(d[4]), "+f"(d[5]), "+f"(d[6]), "+f"(d[7]), "+f"(d[8]), "+f"(d[9]), "+f"(d[10]), "+f"(d[11]), "+f"(d[12]), "+f"(d[13]), "+f"(d[14]), "+f"(d[15]), "+f"(d[16]), "+f"(d[17]), "+f"(d[18]), "+f"(d[19]), "+f"(d[20]), "+f"(d[21]), "+f"(d[22]), "+f"(d[23]), "+f"(d[24]), "+f"(d[25]), "+f"(d[26]), "+f"(d[27]), "+f"(d[28]), "+f"(d[29]), "+f"(d[30]), "+f"(d[31])
        : "r"(a[0]), "r"(a[1]), "r"(a[2]), "r"(a[3]), "l"(b), "r"(scale_d));
}
template <> __device__ __forceinline__ void wgmma_rs<80>(float (&d)[128], const uint32_t (&a)[4], uint64_t b, int scale_d) {
    asm volatile("{\n.reg .pred p;\nsetp.ne.b32 p, %45, 0;\nwgmma.mma_async.sync.aligned.m64n80k16.f32.bf16.bf16 {%0,%1,%2,%3,%4,%5,%6,%7,%8,%9,%10,%11,%12,%13,%14,%15,%16,%17,%18,%19,%20,%21,%22,%23,%24,%25,%26,%27,%28,%29,%30,%31,%32,%33,%34,%35,%36,%37,%38,%39}, {%40,%41,%42,%43}, %44, p, 1, 1, 0;\n}\n"
        : "+f"(d[0]), "+f"(d[1]), "+f"(d[2]), "+f"(d[3]), "+f"(d[4]), "+f"(d[5]), "+f"(d[6]), "+f"(d[7]), "+f"(d[8]), "+f"(d[9]), "+f"(d[10]), "+f"(d[11]), "+f"(d[12]), "+f"(d[13]), "+f"(d[14]), "+f"(d[15]), "+f"(d[16]), "+f"(d[17]), "+f"(d[18]), "+f"(d[19]), "+f"(d[20]), "+f"(d[21]), "+f"(d[22]), "+f"(d[23]), "+f"(d[24]), "+f"(d[25]), "+f"(d[26]), "+f"(d[27]), "+f"(d[28]), "+f"(d[29]), "+f"(d[30]), "+f"(d[31]), "+f"(d[32]), "+f"(d[33]), "+f"(d[34]), "+f"(d[35]), "+f"(d[36]), "+f"(d[37]), "+f"(d[38]), "+f"(d[39])
        : "r"(a[0]), "r"(a[1]), "r"(a[2]), "r"(a[3]), "l"(b), "r"(scale_d));
}
template <> __device__ __forceinline__ void wgmma_rs<96>(float (&d)[128], const uint32_t (&a)[4], uint64_t b, int scale_d) {
    asm volatile("{\n.reg .pred p;\nsetp.ne.b32 p, %53, 0;\nwgmma.mma_async.sync.aligned.m64n96k16.f32.bf16.bf16 {%0,%1,%2,%3,%4,%5,%6,%7,%8,%9,%10,%11,%12,%13,%14,%15,%16,%17,%18,%19,%20,%21,%22,%23,%24,%25,%26,%27,%28,%29,%30,%31,%32,%33,%34,%35,%36,%37,%38,%39,%40,%41,%42,%43,%44,%45,%46,%47}, {%48,%49,%50,%51}, %52, p, 1, 1, 0;\n}\n"
        : "+f"(d[0]), "+f"(d[1]), "+f"(d[2]), "+f"(d[3]), "+f"(d[4]), "+f"(d[5]), "+f"(d[6]), "+f"(d[7]), "+f"(d[8]), "+f"(d[9]), "+f"(d[10]), "+f"(d[11]), "+f"(d[12]), "+f"(d[13]), "+f"(d[14]), "+f"(d[15]), "+f"(d[16]), "+f"(d[17]), "+f"(d[18]), "+f"(d[19]), "+f"(d[20]), "+f"(d[21]), "+f"(d[22]), "+f"(d[23]), "+f"(d[24]), "+f"(d[25]), "+f"(d[26]), "+f"(d[27]), "+f"(d[28]), "+f"(d[29]), "+f"(d[30]), "+f"(d[31]), "+f"(d[32]), "+f"(d[33]), "+f"(d[34]), "+f"(d[35]), "+f"(d[36]), "+f"(d[37]), "+f"(d[38]), "+f"(d[39]), "+f"(d[40]), "+f"(d[41]), "+f"(d[42]), "+f"(d[43]), "+f"(d[44]), "+f"(d[45]), "+f"(d[46]), "+f"(d[47])
        : "r"(a[0]), "r"(a[1]), "r"(a[2]), "r"(a[3]), "l"(b), "r"(scale_d));
}
template <> __device__ __forceinline__ void wgmma_rs<112>(float (&d)[128], const uint32_t (&a)[4], uint64_t b, int scale_d) {
    asm volatile("{\n.reg .pred p;\nsetp.ne.b32 p, %61, 0;\nwgmma.mma_async.sync.aligned.m64n112k16.f32.bf16.bf16 {%0,%1,%2,%3,%4,%5,%6,%7,%8,%9,%10,%11,%12,%13,%14,%15,%16,%17,%18,%19,%20,%21,%22,%23,%24,%25,%26,%27,%28,%29,%30,%31,%32,%33,%34,%35,%36,%37,%38,%39,%40,%41,%42,%43,%44,%45,%46,%47,%48,%49,%50,%51,%52,%53,%54,%55}, {%56,%57,%58,%59}, %60, p, 1, 1, 0;\n}\n"
        : "+f"(d[0]), "+f"(d[1]), "+f"(d[2]), "+f"(d[3]), "+f"(d[4]), "+f"(d[5]), "+f"(d[6]), "+f"(d[7]), "+f"(d[8]), "+f"(d[9]), "+f"(d[10]), "+f"(d[11]), "+f"(d[12]), "+f"(d[13]), "+f"(d[14]), "+f"(d[15]), "+f"(d[16]), "+f"(d[17]), "+f"(d[18]), "+f"(d[19]), "+f"(d[20]), "+f"(d[21]), "+f"(d[22]), "+f"(d[23]), "+f"(d[24]), "+f"(d[25]), "+f"(d[26]), "+f"(d[27]), "+f"(d[28]), "+f"(d[29]), "+f"(d[30]), "+f"(d[31]), "+f"(d[32]), "+f"(d[33]), "+f"(d[34]), "+f"(d[35]), "+f"(d[36]), "+f"(d[37]), "+f"(d[38]), "+f"(d[39]), "+f"(d[40]), "+f"(d[41]), "+f"(d[42]), "+f"(d[43]), "+f"(d[44]), "+f"(d[45]), "+f"(d[46]), "+f"(d[47]), "+f"(d[48]), "+f"(d[49]), "+f"(d[50]), "+f"(d[51]), "+f"(d[52]), "+f"(d[53]), "+f"(d[54]), "+f"(d[55])
        : "r"(a[0]), "r"(a[1]), "r"(a[2]), "r"(a[3]), "l"(b), "r"(scale_d));
}
template <> __device__ __forceinline__ void wgmma_rs<128>(float (&d)[128], const uint32_t (&a)[4], uint64_t b, int scale_d) {
    asm volatile("{\n.reg .pred p;\nsetp.ne.b32 p, %69, 0;\nwgmma.mma_async.sync.aligned.m64n128k16.f32.bf16.bf16 {%0,%1,%2,%3,%4,%5,%6,%7,%8,%9,%10,%11,%12,%13,%14,%15,%16,%17,%18,%19,%20,%21,%22,%23,%24,%25,%26,%27,%28,%29,%30,%31,%32,%33,%34,%35,%36,%37,%38,%39,%40,%41,%42,%43,%44,%45,%46,%47,%48,%49,%50,%51,%52,%53,%54,%55,%56,%57,%58,%59,%60,%61,%62,%63}, {%64,%65,%66,%67}, %68, p, 1, 1, 0;\n}\n"
        : "+f"(d[0]), "+f"(d[1]), "+f"(d[2]), "+f"(d[3]), "+f"(d[4]), "+f"(d[5]), "+f"(d[6]), "+f"(d[7]), "+f"(d[8]), "+f"(d[9]), "+f"(d[10]), "+f"(d[11]), "+f"(d[12]), "+f"(d[13]), "+f"(d[14]), "+f"(d[15]), "+f"(d[16]), "+f"(d[17]), "+f"(d[18]), "+f"(d[19]), "+f"(d[20]), "+f"(d[21]), "+f"(d[22]), "+f"(d[23]), "+f"(d[24]), "+f"(d[25]), "+f"(d[26]), "+f"(d[27]), "+f"(d[28]), "+f"(d[29]), "+f"(d[30]), "+f"(d[31]), "+f"(d[32]), "+f"(d[33]), "+f"(d[34]), "+f"(d[35]), "+f"(d[36]), "+f"(d[37]), "+f"(d[38]), "+f"(d[39]), "+f"(d[40]), "+f"(d[41]), "+f"(d[42]), "+f"(d[43]), "+f"(d[44]), "+f"(d[45]), "+f"(d[46]), "+f"(d[47]), "+f"(d[48]), "+f"(d[49]), "+f"(d[50]), "+f"(d[51]), "+f"(d[52]), "+f"(d[53]), "+f"(d[54]), "+f"(d[55]), "+f"(d[56]), "+f"(d[57]), "+f"(d[58]), "+f"(d[59]), "+f"(d[60]), "+f"(d[61]), "+f"(d[62]), "+f"(d[63])
        : "r"(a[0]), "r"(a[1]), "r"(a[2]), "r"(a[3]), "l"(b), "r"(scale_d));
}
template <> __device__ __forceinline__ void wgmma_rs<144>(float (&d)[128], const uint32_t (&a)[4], uint64_t b, int scale_d) {
    asm volatile("{\n.reg .pred p;\nsetp.ne.b32 p, %77, 0;\nwgmma.mma_async.sync.aligned.m64n144k16.f32.bf16.bf16 {%0,%1,%2,%3,%4,%5,%6,%7,%8,%9,%10,%11,%12,%13,%14,%15,%16,%17,%18,%19,%20,%21,%22,%23,%24,%25,%26,%27,%28,%29,%30,%31,%32,%33,%34,%35,%36,%37,%38,%39,%40,%41,%42,%43,%44,%45,%46,%47,%48,%49,%50,%51,%52,%53,%54,%55,%56,%57,%58,%59,%60,%61,%62,%63,%64,%65,%66,%67,%68,%69,%70,%71}, {%72,%73,%74,%75}, %76, p, 1, 1, 0;\n}\n"
        : "+f"(d[0]), "+f"(d[1]), "+f"(d[2]), "+f"(d[3]), "+f"(d[4]), "+f"(d[5]), "+f"(d[6]), "+f"(d[7]), "+f"(d[8]), "+f"(d[9]), "+f"(d[10]), "+f"(d[11]), "+f"(d[12]), "+f"(d[13]), "+f"(d[14]), "+f"(d[15]), "+f"(d[16]), "+f"(d[17]), "+f"(d[18]), "+f"(d[19]), "+f"(d[20]), "+f"(d[21]), "+f"(d[22]), "+f"(d[23]), "+f"(d[24]), "+f"(d[25]), "+f"(d[26]), "+f"(d[27]), "+f"(d[28]), "+f"(d[29]), "+f"(d[30]), "+f"(d[31]), "+f"(d[32]), "+f"(d[33]), "+f"(d[34]), "+f"(d[35]), "+f"(d[36]), "+f"(d[37]), "+f"(d[38]), "+f"(d[39]), "+f"(d[40]), "+f"(d[41]), "+f"(d[42]), "+f"(d[43]), "+f"(d[44]), "+f"(d[45]), "+f"(d[46]), "+f"(d[47]), "+f"(d[48]), "+f"(d[49]), "+f"(d[50]), "+f"(d[51]), "+f"(d[52]), "+f"(d[53]), "+f"(d[54]), "+f"(d[55]), "+f"(d[56]), "+f"(d[57]), "+f"(d[58]), "+f"(d[59]), "+f"(d[60]), "+f"(d[61]), "+f"(d[62]), "+f"(d[63]), "+f"(d[64]), "+f"(d[65]), "+f"(d[66]), "+f"(d[67]), "+f"(d[68]), "+f"(d[69]), "+f"(d[70]), "+f"(d[71])
        : "r"(a[0]), "r"(a[1]), "r"(a[2]), "r"(a[3]), "l"(b), "r"(scale_d));
}
template <> __device__ __forceinline__ void wgmma_rs<160>(float (&d)[128], const uint32_t (&a)[4], uint64_t b, int scale_d) {
    asm volatile("{\n.reg .pred p;\nsetp.ne.b32 p, %85, 0;\nwgmma.mma_async.sync.aligned.m64n160k16.f32.bf16.bf16 {%0,%1,%2,%3,%4,%5,%6,%7,%8,%9,%10,%11,%12,%13,%14,%15,%16,%17,%18,%19,%20,%21,%22,%23,%24,%25,%26,%27,%28,%29,%30,%31,%32,%33,%34,%35,%36,%37,%38,%39,%40,%41,%42,%43,%44,%45,%46,%47,%48,%49,%50,%51,%52,%53,%54,%55,%56,%57,%58,%59,%60,%61,%62,%63,%64,%65,%66,%67,%68,%69,%70,%71,%72,%73,%74,%75,%76,%77,%78,%79}, {%80,%81,%82,%83}, %84, p, 1, 1, 0;\n}\n"
        : "+f"(d[0]), "+f"(d[1]), "+f"(d[2]), "+f"(d[3]), "+f"(d[4]), "+f"(d[5]), "+f"(d[6]), "+f"(d[7]), "+f"(d[8]), "+f"(d[9]), "+f"(d[10]), "+f"(d[11]), "+f"(d[12]), "+f"(d[13]), "+f"(d[14]), "+f"(d[15]), "+f"(d[16]), "+f"(d[17]), "+f"(d[18]), "+f"(d[19]), "+f"(d[20]), "+f"(d[21]), "+f"(d[22]), "+f"(d[23]), "+f"(d[24]), "+f"(d[25]), "+f"(d[26]), "+f"(d[27]), "+f"(d[28]), "+f"(d[29]), "+f"(d[30]), "+f"(d[31]), "+f"(d[32]), "+f"(d[33]), "+f"(d[34]), "+f"(d[35]), "+f"(d[36]), "+f"(d[37]), "+f"(d[38]), "+f"(d[39]), "+f"(d[40]), "+f"(d[41]), "+f"(d[42]), "+f"(d[43]), "+f"(d[44]), "+f"(d[45]), "+f"(d[46]), "+f"(d[47]), "+f"(d[48]), "+f"(d[49]), "+f"(d[50]), "+f"(d[51]), "+f"(d[52]), "+f"(d[53]), "+f"(d[54]), "+f"(d[55]), "+f"(d[56]), "+f"(d[57]), "+f"(d[58]), "+f"(d[59]), "+f"(d[60]), "+f"(d[61]), "+f"(d[62]), "+f"(d[63]), "+f"(d[64]), "+f"(d[65]), "+f"(d[66]), "+f"(d[67]), "+f"(d[68]), "+f"(d[69]), "+f"(d[70]), "+f"(d[71]), "+f"(d[72]), "+f"(d[73]), "+f"(d[74]), "+f"(d[75]), "+f"(d[76]), "+f"(d[77]), "+f"(d[78]), "+f"(d[79])
        : "r"(a[0]), "r"(a[1]), "r"(a[2]), "r"(a[3]), "l"(b), "r"(scale_d));
}
template <> __device__ __forceinline__ void wgmma_rs<176>(float (&d)[128], const uint32_t (&a)[4], uint64_t b, int scale_d) {
    asm volatile("{\n.reg .pred p;\nsetp.ne.b32 p, %93, 0;\nwgmma.mma_async.sync.aligned.m64n176k16.f32.bf16.bf16 {%0,%1,%2,%3,%4,%5,%6,%7,%8,%9,%10,%11,%12,%13,%14,%15,%16,%17,%18,%19,%20,%21,%22,%23,%24,%25,%26,%27,%28,%29,%30,%31,%32,%33,%34,%35,%36,%37,%38,%39,%40,%41,%42,%43,%44,%45,%46,%47,%48,%49,%50,%51,%52,%53,%54,%55,%56,%57,%58,%59,%60,%61,%62,%63,%64,%65,%66,%67,%68,%69,%70,%71,%72,%73,%74,%75,%76,%77,%78,%79,%80,%81,%82,%83,%84,%85,%86,%87}, {%88,%89,%90,%91}, %92, p, 1, 1, 0;\n}\n"
        : "+f"(d[0]), "+f"(d[1]), "+f"(d[2]), "+f"(d[3]), "+f"(d[4]), "+f"(d[5]), "+f"(d[6]), "+f"(d[7]), "+f"(d[8]), "+f"(d[9]), "+f"(d[10]), "+f"(d[11]), "+f"(d[12]), "+f"(d[13]), "+f"(d[14]), "+f"(d[15]), "+f"(d[16]), "+f"(d[17]), "+f"(d[18]), "+f"(d[19]), "+f"(d[20]), "+f"(d[21]), "+f"(d[22]), "+f"(d[23]), "+f"(d[24]), "+f"(d[25]), "+f"(d[26]), "+f"(d[27]), "+f"(d[28]), "+f"(d[29]), "+f"(d[30]), "+f"(d[31]), "+f"(d[32]), "+f"(d[33]), "+f"(d[34]), "+f"(d[35]), "+f"(d[36]), "+f"(d[37]), "+f"(d[38]), "+f"(d[39]), "+f"(d[40]), "+f"(d[41]), "+f"(d[42]), "+f"(d[43]), "+f"(d[44]), "+f"(d[45]), "+f"(d[46]), "+f"(d[47]), "+f"(d[48]), "+f"(d[49]), "+f"(d[50]), "+f"(d[51]), "+f"(d[52]), "+f"(d[53]), "+f"(d[54]), "+f"(d[55]), "+f"(d[56]), "+f"(d[57]), "+f"(d[58]), "+f"(d[59]), "+f"(d[60]), "+f"(d[61]), "+f"(d[62]), "+f"(d[63]), "+f"(d[64]), "+f"(d[65]), "+f"(d[66]), "+f"(d[67]), "+f"(d[68]), "+f"(d[69]), "+f"(d[70]), "+f"(d[71]), "+f"(d[72]), "+f"(d[73]), "+f"(d[74]), "+f"(d[75]), "+f"(d[76]), "+f"(d[77]), "+f"(d[78]), "+f"(d[79]), "+f"(d[80]), "+f"(d[81]), "+f"(d[82]), "+f"(d[83]), "+f"(d[84]), "+f"(d[85]), "+f"(d[86]), "+f"(d[87])
        : "r"(a[0]), "r"(a[1]), "r"(a[2]), "r"(a[3]), "l"(b), "r"(scale_d));
}
template <> __device__ __forceinline__ void wgmma_rs<192>(float (&d)[128], const uint32_t (&a)[4], uint64_t b, int scale_d) {
    asm volatile("{\n.reg .pred p;\nsetp.ne.b32 p, %101, 0;\nwgmma.mma_async.sync.aligned.m64n192k16.f32.bf16.bf16 {%0,%1,%2,%3,%4,%5,%6,%7,%8,%9,%10,%11,%12,%13,%14,%15,%16,%17,%18,%19,%20,%21,%22,%23,%24,%25,%26,%27,%28,%29,%30,%31,%32,%33,%34,%35,%36,%37,%38,%39,%40,%41,%42,%43,%44,%45,%46,%47,%48,%49,%50,%51,%52,%53,%54,%55,%56,%57,%58,%59,%60,%61,%62,%63,%64,%65,%66,%67,%68,%69,%70,%71,%72,%73,%74,%75,%76,%77,%78,%79,%80,%81,%82,%83,%84,%85,%86,%87,%88,%89,%90,%91,%92,%93,%94,%95}, {%96,%97,%98,%99}, %100, p, 1, 1, 0;\n}\n"
        : "+f"(d[0]), "+f"(d[1]), "+f"(d[2]), "+f"(d[3]), "+f"(d[4]), "+f"(d[5]), "+f"(d[6]), "+f"(d[7]), "+f"(d[8]), "+f"(d[9]), "+f"(d[10]), "+f"(d[11]), "+f"(d[12]), "+f"(d[13]), "+f"(d[14]), "+f"(d[15]), "+f"(d[16]), "+f"(d[17]), "+f"(d[18]), "+f"(d[19]), "+f"(d[20]), "+f"(d[21]), "+f"(d[22]), "+f"(d[23]), "+f"(d[24]), "+f"(d[25]), "+f"(d[26]), "+f"(d[27]), "+f"(d[28]), "+f"(d[29]), "+f"(d[30]), "+f"(d[31]), "+f"(d[32]), "+f"(d[33]), "+f"(d[34]), "+f"(d[35]), "+f"(d[36]), "+f"(d[37]), "+f"(d[38]), "+f"(d[39]), "+f"(d[40]), "+f"(d[41]), "+f"(d[42]), "+f"(d[43]), "+f"(d[44]), "+f"(d[45]), "+f"(d[46]), "+f"(d[47]), "+f"(d[48]), "+f"(d[49]), "+f"(d[50]), "+f"(d[51]), "+f"(d[52]), "+f"(d[53]), "+f"(d[54]), "+f"(d[55]), "+f"(d[56]), "+f"(d[57]), "+f"(d[58]), "+f"(d[59]), "+f"(d[60]), "+f"(d[61]), "+f"(d[62]), "+f"(d[63]), "+f"(d[64]), "+f"(d[65]), "+f"(d[66]), "+f"(d[67]), "+f"(d[68]), "+f"(d[69]), "+f"(d[70]), "+f"(d[71]), "+f"(d[72]), "+f"(d[73]), "+f"(d[74]), "+f"(d[75]), "+f"(d[76]), "+f"(d[77]), "+f"(d[78]), "+f"(d[79]), "+f"(d[80]), "+f"(d[81]), "+f"(d[82]), "+f"(d[83]), "+f"(d[84]), "+f"(d[85]), "+f"(d[86]), "+f"(d[87]), "+f"(d[88]), "+f"(d[89]), "+f"(d[90]), "+f"(d[91]), "+f"(d[92]), "+f"(d[93]), "+f"(d[94]), "+f"(d[95])
        : "r"(a[0]), "r"(a[1]), "r"(a[2]), "r"(a[3]), "l"(b), "r"(scale_d));
}
template <> __device__ __forceinline__ void wgmma_rs<208>(float (&d)[128], const uint32_t (&a)[4], uint64_t b, int scale_d) {
    asm volatile("{\n.reg .pred p;\nsetp.ne.b32 p, %109, 0;\nwgmma.mma_async.sync.aligned.m64n208k16.f32.bf16.bf16 {%0,%1,%2,%3,%4,%5,%6,%7,%8,%9,%10,%11,%12,%13,%14,%15,%16,%17,%18,%19,%20,%21,%22,%23,%24,%25,%26,%27,%28,%29,%30,%31,%32,%33,%34,%35,%36,%37,%38,%39,%40,%41,%42,%43,%44,%45,%46,%47,%48,%49,%50,%51,%52,%53,%54,%55,%56,%57,%58,%59,%60,%61,%62,%63,%64,%65,%66,%67,%68,%69,%70,%71,%72,%73,%74,%75,%76,%77,%78,%79,%80,%81,%82,%83,%84,%85,%86,%87,%88,%89,%90,%91,%92,%93,%94,%95,%96,%97,%98,%99,%100,%101,%102,%103}, {%104,%105,%106,%107}, %108, p, 1, 1, 0;\n}\n"
        : "+f"(d[0]), "+f"(d[1]), "+f"(d[2]), "+f"(d[3]), "+f"(d[4]), "+f"(d[5]), "+f"(d[6]), "+f"(d[7]), "+f"(d[8]), "+f"(d[9]), "+f"(d[10]), "+f"(d[11]), "+f"(d[12]), "+f"(d[13]), "+f"(d[14]), "+f"(d[15]), "+f"(d[16]), "+f"(d[17]), "+f"(d[18]), "+f"(d[19]), "+f"(d[20]), "+f"(d[21]), "+f"(d[22]), "+f"(d[23]), "+f"(d[24]), "+f"(d[25]), "+f"(d[26]), "+f"(d[27]), "+f"(d[28]), "+f"(d[29]), "+f"(d[30]), "+f"(d[31]), "+f"(d[32]), "+f"(d[33]), "+f"(d[34]), "+f"(d[35]), "+f"(d[36]), "+f"(d[37]), "+f"(d[38]), "+f"(d[39]), "+f"(d[40]), "+f"(d[41]), "+f"(d[42]), "+f"(d[43]), "+f"(d[44]), "+f"(d[45]), "+f"(d[46]), "+f"(d[47]), "+f"(d[48]), "+f"(d[49]), "+f"(d[50]), "+f"(d[51]), "+f"(d[52]), "+f"(d[53]), "+f"(d[54]), "+f"(d[55]), "+f"(d[56]), "+f"(d[57]), "+f"(d[58]), "+f"(d[59]), "+f"(d[60]), "+f"(d[61]), "+f"(d[62]), "+f"(d[63]), "+f"(d[64]), "+f"(d[65]), "+f"(d[66]), "+f"(d[67]), "+f"(d[68]), "+f"(d[69]), "+f"(d[70]), "+f"(d[71]), "+f"(d[72]), "+f"(d[73]), "+f"(d[74]), "+f"(d[75]), "+f"(d[76]), "+f"(d[77]), "+f"(d[78]), "+f"(d[79]), "+f"(d[80]), "+f"(d[81]), "+f"(d[82]), "+f"(d[83]), "+f"(d[84]), "+f"(d[85]), "+f"(d[86]), "+f"(d[87]), "+f"(d[88]), "+f"(d[89]), "+f"(d[90]), "+f"(d[91]), "+f"(d[92]), "+f"(d[93]), "+f"(d[94]), "+f"(d[95]), "+f"(d[96]), "+f"(d[97]), "+f"(d[98]), "+f"(d[99]), "+f"(d[100]), "+f"(d[101]), "+f"(d[102]), "+f"(d[103])
        : "r"(a[0]), "r"(a[1]), "r"(a[2]), "r"(a[3]), "l"(b), "r"(scale_d));
}
template <> __device__ __forceinline__ void wgmma_rs<224>(float (&d)[128], const uint32_t (&a)[4], uint64_t b, int scale_d) {
    asm volatile("{\n.reg .pred p;\nsetp.ne.b32 p, %117, 0;\nwgmma.mma_async.sync.aligned.m64n224k16.f32.bf16.bf16 {%0,%1,%2,%3,%4,%5,%6,%7,%8,%9,%10,%11,%12,%13,%14,%15,%16,%17,%18,%19,%20,%21,%22,%23,%24,%25,%26,%27,%28,%29,%30,%31,%32,%33,%34,%35,%36,%37,%38,%39,%40,%41,%42,%43,%44,%45,%46,%47,%48,%49,%50,%51,%52,%53,%54,%55,%56,%57,%58,%59,%60,%61,%62,%63,%64,%65,%66,%67,%68,%69,%70,%71,%72,%73,%74,%75,%76,%77,%78,%79,%80,%81,%82,%83,%84,%85,%86,%87,%88,%89,%90,%91,%92,%93,%94,%95,%96,%97,%98,%99,%100,%101,%102,%103,%104,%105,%106,%107,%108,%109,%110,%111}, {%112,%113,%114,%115}, %116, p, 1, 1, 0;\n}\n"
        : "+f"(d[0]), "+f"(d[1]), "+f"(d[2]), "+f"(d[3]), "+f"(d[4]), "+f"(d[5]), "+f"(d[6]), "+f"(d[7]), "+f"(d[8]), "+f"(d[9]), "+f"(d[10]), "+f"(d[11]), "+f"(d[12]), "+f"(d[13]), "+f"(d[14]), "+f"(d[15]), "+f"(d[16]), "+f"(d[17]), "+f"(d[18]), "+f"(d[19]), "+f"(d[20]), "+f"(d[21]), "+f"(d[22]), "+f"(d[23]), "+f"(d[24]), "+f"(d[25]), "+f"(d[26]), "+f"(d[27]), "+f"(d[28]), "+f"(d[29]), "+f"(d[30]), "+f"(d[31]), "+f"(d[32]), "+f"(d[33]), "+f"(d[34]), "+f"(d[35]), "+f"(d[36]), "+f"(d[37]), "+f"(d[38]), "+f"(d[39]), "+f"(d[40]), "+f"(d[41]), "+f"(d[42]), "+f"(d[43]), "+f"(d[44]), "+f"(d[45]), "+f"(d[46]), "+f"(d[47]), "+f"(d[48]), "+f"(d[49]), "+f"(d[50]), "+f"(d[51]), "+f"(d[52]), "+f"(d[53]), "+f"(d[54]), "+f"(d[55]), "+f"(d[56]), "+f"(d[57]), "+f"(d[58]), "+f"(d[59]), "+f"(d[60]), "+f"(d[61]), "+f"(d[62]), "+f"(d[63]), "+f"(d[64]), "+f"(d[65]), "+f"(d[66]), "+f"(d[67]), "+f"(d[68]), "+f"(d[69]), "+f"(d[70]), "+f"(d[71]), "+f"(d[72]), "+f"(d[73]), "+f"(d[74]), "+f"(d[75]), "+f"(d[76]), "+f"(d[77]), "+f"(d[78]), "+f"(d[79]), "+f"(d[80]), "+f"(d[81]), "+f"(d[82]), "+f"(d[83]), "+f"(d[84]), "+f"(d[85]), "+f"(d[86]), "+f"(d[87]), "+f"(d[88]), "+f"(d[89]), "+f"(d[90]), "+f"(d[91]), "+f"(d[92]), "+f"(d[93]), "+f"(d[94]), "+f"(d[95]), "+f"(d[96]), "+f"(d[97]), "+f"(d[98]), "+f"(d[99]), "+f"(d[100]), "+f"(d[101]), "+f"(d[102]), "+f"(d[103]), "+f"(d[104]), "+f"(d[105]), "+f"(d[106]), "+f"(d[107]), "+f"(d[108]), "+f"(d[109]), "+f"(d[110]), "+f"(d[111])
        : "r"(a[0]), "r"(a[1]), "r"(a[2]), "r"(a[3]), "l"(b), "r"(scale_d));
}
template <> __device__ __forceinline__ void wgmma_rs<240>(float (&d)[128], const uint32_t (&a)[4], uint64_t b, int scale_d) {
    asm volatile("{\n.reg .pred p;\nsetp.ne.b32 p, %125, 0;\nwgmma.mma_async.sync.aligned.m64n240k16.f32.bf16.bf16 {%0,%1,%2,%3,%4,%5,%6,%7,%8,%9,%10,%11,%12,%13,%14,%15,%16,%17,%18,%19,%20,%21,%22,%23,%24,%25,%26,%27,%28,%29,%30,%31,%32,%33,%34,%35,%36,%37,%38,%39,%40,%41,%42,%43,%44,%45,%46,%47,%48,%49,%50,%51,%52,%53,%54,%55,%56,%57,%58,%59,%60,%61,%62,%63,%64,%65,%66,%67,%68,%69,%70,%71,%72,%73,%74,%75,%76,%77,%78,%79,%80,%81,%82,%83,%84,%85,%86,%87,%88,%89,%90,%91,%92,%93,%94,%95,%96,%97,%98,%99,%100,%101,%102,%103,%104,%105,%106,%107,%108,%109,%110,%111,%112,%113,%114,%115,%116,%117,%118,%119}, {%120,%121,%122,%123}, %124, p, 1, 1, 0;\n}\n"
        : "+f"(d[0]), "+f"(d[1]), "+f"(d[2]), "+f"(d[3]), "+f"(d[4]), "+f"(d[5]), "+f"(d[6]), "+f"(d[7]), "+f"(d[8]), "+f"(d[9]), "+f"(d[10]), "+f"(d[11]), "+f"(d[12]), "+f"(d[13]), "+f"(d[14]), "+f"(d[15]), "+f"(d[16]), "+f"(d[17]), "+f"(d[18]), "+f"(d[19]), "+f"(d[20]), "+f"(d[21]), "+f"(d[22]), "+f"(d[23]), "+f"(d[24]), "+f"(d[25]), "+f"(d[26]), "+f"(d[27]), "+f"(d[28]), "+f"(d[29]), "+f"(d[30]), "+f"(d[31]), "+f"(d[32]), "+f"(d[33]), "+f"(d[34]), "+f"(d[35]), "+f"(d[36]), "+f"(d[37]), "+f"(d[38]), "+f"(d[39]), "+f"(d[40]), "+f"(d[41]), "+f"(d[42]), "+f"(d[43]), "+f"(d[44]), "+f"(d[45]), "+f"(d[46]), "+f"(d[47]), "+f"(d[48]), "+f"(d[49]), "+f"(d[50]), "+f"(d[51]), "+f"(d[52]), "+f"(d[53]), "+f"(d[54]), "+f"(d[55]), "+f"(d[56]), "+f"(d[57]), "+f"(d[58]), "+f"(d[59]), "+f"(d[60]), "+f"(d[61]), "+f"(d[62]), "+f"(d[63]), "+f"(d[64]), "+f"(d[65]), "+f"(d[66]), "+f"(d[67]), "+f"(d[68]), "+f"(d[69]), "+f"(d[70]), "+f"(d[71]), "+f"(d[72]), "+f"(d[73]), "+f"(d[74]), "+f"(d[75]), "+f"(d[76]), "+f"(d[77]), "+f"(d[78]), "+f"(d[79]), "+f"(d[80]), "+f"(d[81]), "+f"(d[82]), "+f"(d[83]), "+f"(d[84]), "+f"(d[85]), "+f"(d[86]), "+f"(d[87]), "+f"(d[88]), "+f"(d[89]), "+f"(d[90]), "+f"(d[91]), "+f"(d[92]), "+f"(d[93]), "+f"(d[94]), "+f"(d[95]), "+f"(d[96]), "+f"(d[97]), "+f"(d[98]), "+f"(d[99]), "+f"(d[100]), "+f"(d[101]), "+f"(d[102]), "+f"(d[103]), "+f"(d[104]), "+f"(d[105]), "+f"(d[106]), "+f"(d[107]), "+f"(d[108]), "+f"(d[109]), "+f"(d[110]), "+f"(d[111]), "+f"(d[112]), "+f"(d[113]), "+f"(d[114]), "+f"(d[115]), "+f"(d[116]), "+f"(d[117]), "+f"(d[118]), "+f"(d[119])
        : "r"(a[0]), "r"(a[1]), "r"(a[2]), "r"(a[3]), "l"(b), "r"(scale_d));
}
template <> __device__ __forceinline__ void wgmma_rs<256>(float (&d)[128], const uint32_t (&a)[4], uint64_t b, int scale_d) {
    asm volatile("{\n.reg .pred p;\nsetp.ne.b32 p, %133, 0;\nwgmma.mma_async.sync.aligned.m64n256k16.f32.bf16.bf16 {%0,%1,%2,%3,%4,%5,%6,%7,%8,%9,%10,%11,%12,%13,%14,%15,%16,%17,%18,%19,%20,%21,%22,%23,%24,%25,%26,%27,%28,%29,%30,%31,%32,%33,%34,%35,%36,%37,%38,%39,%40,%41,%42,%43,%44,%45,%46,%47,%48,%49,%50,%51,%52,%53,%54,%55,%56,%57,%58,%59,%60,%61,%62,%63,%64,%65,%66,%67,%68,%69,%70,%71,%72,%73,%74,%75,%76,%77,%78,%79,%80,%81,%82,%83,%84,%85,%86,%87,%88,%89,%90,%91,%92,%93,%94,%95,%96,%97,%98,%99,%100,%101,%102,%103,%104,%105,%106,%107,%108,%109,%110,%111,%112,%113,%114,%115,%116,%117,%118,%119,%120,%121,%122,%123,%124,%125,%126,%127}, {%128,%129,%130,%131}, %132, p, 1, 1, 0;\n}\n"
        : "+f"(d[0]), "+f"(d[1]), "+f"(d[2]), "+f"(d[3]), "+f"(d[4]), "+f"(d[5]), "+f"(d[6]), "+f"(d[7]), "+f"(d[8]), "+f"(d[9]), "+f"(d[10]), "+f"(d[11]), "+f"(d[12]), "+f"(d[13]), "+f"(d[14]), "+f"(d[15]), "+f"(d[16]), "+f"(d[17]), "+f"(d[18]), "+f"(d[19]), "+f"(d[20]), "+f"(d[21]), "+f"(d[22]), "+f"(d[23]), "+f"(d[24]), "+f"(d[25]), "+f"(d[26]), "+f"(d[27]), "+f"(d[28]), "+f"(d[29]), "+f"(d[30]), "+f"(d[31]), "+f"(d[32]), "+f"(d[33]), "+f"(d[34]), "+f"(d[35]), "+f"(d[36]), "+f"(d[37]), "+f"(d[38]), "+f"(d[39]), "+f"(d[40]), "+f"(d[41]), "+f"(d[42]), "+f"(d[43]), "+f"(d[44]), "+f"(d[45]), "+f"(d[46]), "+f"(d[47]), "+f"(d[48]), "+f"(d[49]), "+f"(d[50]), "+f"(d[51]), "+f"(d[52]), "+f"(d[53]), "+f"(d[54]), "+f"(d[55]), "+f"(d[56]), "+f"(d[57]), "+f"(d[58]), "+f"(d[59]), "+f"(d[60]), "+f"(d[61]), "+f"(d[62]), "+f"(d[63]), "+f"(d[64]), "+f"(d[65]), "+f"(d[66]), "+f"(d[67]), "+f"(d[68]), "+f"(d[69]), "+f"(d[70]), "+f"(d[71]), "+f"(d[72]), "+f"(d[73]), "+f"(d[74]), "+f"(d[75]), "+f"(d[76]), "+f"(d[77]), "+f"(d[78]), "+f"(d[79]), "+f"(d[80]), "+f"(d[81]), "+f"(d[82]), "+f"(d[83]), "+f"(d[84]), "+f"(d[85]), "+f"(d[86]), "+f"(d[87]), "+f"(d[88]), "+f"(d[89]), "+f"(d[90]), "+f"(d[91]), "+f"(d[92]), "+f"(d[93]), "+f"(d[94]), "+f"(d[95]), "+f"(d[96]), "+f"(d[97]), "+f"(d[98]), "+f"(d[99]), "+f"(d[100]), "+f"(d[101]), "+f"(d[102]), "+f"(d[103]), "+f"(d[104]), "+f"(d[105]), "+f"(d[106]), "+f"(d[107]), "+f"(d[108]), "+f"(d[109]), "+f"(d[110]), "+f"(d[111]), "+f"(d[112]), "+f"(d[113]), "+f"(d[114]), "+f"(d[115]), "+f"(d[116]), "+f"(d[117]), "+f"(d[118]), "+f"(d[119]), "+f"(d[120]), "+f"(d[121]), "+f"(d[122]), "+f"(d[123]), "+f"(d[124]), "+f"(d[125]), "+f"(d[126]), "+f"(d[127])
        : "r"(a[0]), "r"(a[1]), "r"(a[2]), "r"(a[3]), "l"(b), "r"(scale_d));
}

template <int I> __device__ __forceinline__ void conv_load_a(uint32_t (&a)[16][4], uint32_t hx0, uint32_t hx1) {
    a[I][0] = lds32_o<-256 * I>(hx0); a[I][1] = lds32_o<-256 * I - 128>(hx0); a[I][2] = lds32_o<-256 * I>(hx1); a[I][3] = lds32_o<-256 * I - 128>(hx1);
    if constexpr (I < 15) conv_load_a<I + 1>(a, hx0, hx1);
}
template <int I> __device__ __forceinline__ void conv_issue(float (&acc)[128], const uint32_t (&a)[16][4], uint64_t db) {
    wgmma_rs<256 - 16 * I>(acc, a[I], db + 16 * I, I != 0);
    if constexpr (I < 15) conv_issue<I + 1>(acc, a, db);
}
template <int G> __device__ __forceinline__ void conv_store_part(const float (&acc)[128], const uint32_t (&wb)[4], bool first_ok) {
    float z0 = acc[4 * G], z1 = acc[4 * G + 1];
    if constexpr (G < 31) { z0 += acc[4 * G + 6]; z1 += acc[4 * G + 7]; }
    if (G > 0 || first_ok) sts64f_o<-128 * (G >> 2)>(wb[G & 3], z1, z0);
    if constexpr (G < 31) conv_store_part<G + 1>(acc, wb, first_ok);
}

__device__ __forceinline__ void kv_cta(const Params& p, uint32_t sb, int j) {
    constexpr uint32_t IN_BYTES = 17408 + 16384, OFF_V = 17408;
    constexpr uint32_t OFF_OUT = 4 * IN_BYTES, OFF_TAPS = OFF_OUT + 4 * 16384;
    constexpr uint32_t B_INF = 0, B_INE = 32, B_OUTF = 64, B_OUTE = 96;
    const uint32_t bars = sb + OFF_BAR;
    const int tid = threadIdx.x, lane = tid & 31;
    if (tid == 0) {
        for (int s = 0; s < 4; s++) { mbar_init(bars + B_INF + 8 * s, 1); mbar_init(bars + B_INE + 8 * s, 8); mbar_init(bars + B_OUTF + 8 * s, 8); mbar_init(bars + B_OUTE + 8 * s, 1); }
        asm volatile("fence.mbarrier_init.release.cluster;" ::: "memory");
    }
    for (int i = tid; i < 512; i += 384) { const uint4 t = __ldg(reinterpret_cast<const uint4*>(p.shift_k) + i); sts128(sb + OFF_TAPS + i * 16, t.x, t.y, t.z, t.w); }
    __syncthreads();
    if (tid == 0) {
        const uint64_t pol = policy_evict_first();
#pragma unroll 1
        for (int i = 0; i < 64 + 3; i++) {
            if (i < 64) {
                const int bf = i & 3, t0 = j * 512 + (i >> 3) * 64, c0 = (i & 7) * 128;
                if (i >= 4) mbar_wait(bars + B_INE + 8 * bf, ((i >> 2) - 1) & 1);
                mbar_expect_tx(bars + B_INF + 8 * bf, 67 * 256 + 64 * 256);
                tma_2d_h(sb + bf * IN_BYTES, &p.tmK, c0, t0 - 3, bars + B_INF + 8 * bf, pol);
                tma_2d_h(sb + bf * IN_BYTES + OFF_V, &p.tmV, c0, t0, bars + B_INF + 8 * bf, pol);
            }
            if (i >= 3) {
                const int o = i - 3, bf = o & 3;
                mbar_wait(bars + B_OUTF + 8 * bf, (o >> 2) & 1);
                if ((o & 7) == 0) H3_GSTAMP(o >> 3);
                tma_store_2d(&p.tmKvT, sb + OFF_OUT + bf * 16384, 1984 - (j * 512 + (o >> 3) * 64), (o & 7) * 128);
                bulk_commit();
                asm volatile("cp.async.bulk.wait_group.read 1;" ::: "memory");
                if (o > 0) mbar_arrive(bars + B_OUTE + 8 * ((o - 1) & 3));
            }
        }
        bulk_wait_all();
        flag_add_after_bulk(p.flags + FL_KV * FLAG_STRIDE);
        H3_GSTAMP(31);
    } else if (tid >= 32) {
#pragma unroll 1
        for (int u = (tid >> 5) - 1; u < 512; u += 11) {
            const int i = u >> 3, bf = i & 3, o = u & 7;
            mbar_wait(bars + B_INF + 8 * bf, (i >> 2) & 1);
            if (i >= 4) mbar_wait(bars + B_OUTE + 8 * bf, ((i >> 2) - 1) & 1);
            const uint32_t out = sb + OFF_OUT + bf * 16384;
            const uint32_t odd = (lane >> 2) & 1, sel0 = odd ? 0x7632u : 0x5410u, sel1 = odd ? 0x5410u : 0x7632u;
            uint32_t kk[2][11], vv[2][8];
            uint4 sw[2];
#pragma unroll
            for (int it = 0; it < 2; it++) {
                const uint32_t rd = sb + bf * IN_BYTES + o * 8 * 256 + (it * 32 + lane) * 4;
#pragma unroll
                for (int r = 0; r < 11; r++) kk[it][r] = lds32(rd + r * 256);
#pragma unroll
                for (int r = 0; r < 8; r++) vv[it][r] = lds32(rd + OFF_V + r * 256);
                sw[it] = lds128(sb + OFF_TAPS + ((i & 7) * 64 + it * 32 + lane) * 16);
            }
#pragma unroll
            for (int it = 0; it < 2; it++) {
                const uint32_t w0 = __byte_perm(sw[it].x, sw[it].z, 0x5410), w1 = __byte_perm(sw[it].x, sw[it].z, 0x7632);
                const uint32_t w2 = __byte_perm(sw[it].y, sw[it].w, 0x5410), w3 = __byte_perm(sw[it].y, sw[it].w, 0x7632);
#pragma unroll
                for (int r = 0; r < 8; r++)
                    vv[it][r] = bf2_mul(bf2_add(bf2_add(bf2_add(bf2_mul(kk[it][r], w3), bf2_mul(kk[it][r + 1], w2)), bf2_mul(kk[it][r + 2], w1)), bf2_mul(kk[it][r + 3], w0)), vv[it][r]);
                const uint32_t r0 = 2 * (it * 32 + lane) + odd, r1 = r0 ^ 1;
                const uint32_t* v = vv[it];
                sts128(out + r0 * 128 + (((7 - o) ^ (r0 & 7)) << 4), __byte_perm(v[0], v[1], sel0), __byte_perm(v[2], v[3], sel0), __byte_perm(v[4], v[5], sel0), __byte_perm(v[6], v[7], sel0));
                sts128(out + r1 * 128 + (((7 - o) ^ (r1 & 7)) << 4), __byte_perm(v[0], v[1], sel1), __byte_perm(v[2], v[3], sel1), __byte_perm(v[4], v[5], sel1), __byte_perm(v[6], v[7], sel1));
            }
            fence_async_smem();
            __syncwarp();
            if (lane == 0) { mbar_arrive(bars + B_INE + 8 * bf); mbar_arrive(bars + B_OUTF + 8 * bf); }
        }
    }
}

__global__ void __launch_bounds__(384, 1) h3_kernel(const __grid_constant__ Params p) {
    extern __shared__ uint8_t smem_raw[];
    const uint32_t sb = (smem_u32(smem_raw) + 1023) & ~1023u;
    const uint32_t bars = sb + OFF_BAR;
    const int tid = threadIdx.x;
    const int wg = __shfl_sync(0xffffffffu, tid >> 7, 0);
    const int lane = tid & 31;
    const int cta = blockIdx.x;
    const int pair = cta >> 1;
    const uint32_t rank = cta & 1;

    if (cta >= NCTA) { kv_cta(p, sb, cta - NCTA); return; }

    uint32_t x[32];
    if (wg != 0) {
        const uint4* src = reinterpret_cast<const uint4*>(p.q + (size_t)(cta * 16 + ((tid >> 5) - 4) * 2 + (lane >> 4)) * D) + (lane & 15);
#pragma unroll
        for (int i = 0; i < 8; i++) { const uint4 t = __ldg(src + i * 16); x[4 * i] = t.x; x[4 * i + 1] = t.y; x[4 * i + 2] = t.z; x[4 * i + 3] = t.w; }
    }
    if (tid == 0) {
        H3_STAMP(0);
#pragma unroll 1
        for (int s = 0; s < 4; s++) { mbar_init(bars + BAR_FULLA + 8 * s, 1); mbar_init(bars + BAR_EMPTYA + 8 * s, 2); mbar_init(bars + BAR_FINALA + 8 * s, 4); }
#pragma unroll 1
        for (int s = 0; s < 6; s++) { mbar_init(bars + BAR_FULLB + 8 * s, 1); mbar_init(bars + BAR_EMPTYB + 8 * s, 4); }
        mbar_init(bars + BAR_STGFULL, 8);
        mbar_init(bars + BAR_STGEMPTY, 1);
        mbar_init(bars + BAR_ALTFULL, 8);
        mbar_init(bars + BAR_ALT2FULL, 8);
        mbar_init(bars + BAR_REDFREE, 4);
        mbar_init(bars + BAR_OPFULL, 1);
        asm volatile("fence.mbarrier_init.release.cluster;" ::: "memory");
    }
    __syncthreads();
    cluster_arrive();

    const int m1 = cta & 15;
    const int nb1 = cta >> 4;
    const int m2 = pair >> 2;
    const int nh = 24 + (pair & 3);
    const int n2 = (pair & 3) * 256 + (int)rank * 128;

    if (wg == 0) {
        asm volatile("setmaxnreg.dec.sync.aligned.u32 56;\n");
        const int warp = tid >> 5;
        if (warp == 0) {
            if (lane == 0) {
                const uint64_t pol = policy_evict_first();
                const int mrow1 = m1 * 128, mrow2 = m2 * 128 + (int)rank * 64, ngh = nh * 2 + (int)rank;
#pragma unroll 1
                for (int j = 0; j < 4; j++) {
                    const uint32_t full = bars + BAR_FULLA + 8 * j;
                    mbar_expect_tx(full, A_STAGE);
                    tma_3d_h(sb + j * A_STAGE + 16384, &p.tmWg2, 0, j * 64, nb1 * 2, full, pol);
                    tma_3d_h(sb + j * A_STAGE + 32768, &p.tmWu2, 0, j * 64, nb1 * 2, full, pol);
                }
                flag_wait(p.flags + (FL_XN + m1) * FLAG_STRIDE, 64);
                H3_STAMP(1);
#pragma unroll 1
                for (int j = 0; j < 4; j++) tma_2d(sb + j * A_STAGE, &p.tmXn128, j * 64, mrow1, bars + BAR_FULLA + 8 * j);
                if (m1 >= 4 && m1 < 12) { pf_3d_h(&p.tmWg2, 0, m1 * 64, nb1 * 2, pol); pf_3d_h(&p.tmWu2, 0, m1 * 64, nb1 * 2, pol); }
#pragma unroll 1
                for (int g = 4; g < 48; g++) {
                    const int st = g & 3, k0 = (g & 15) * 64, ng = ((g >> 4) * 8 + nb1) * 2;
                    const uint32_t full = bars + BAR_FULLA + 8 * st, a = sb + st * A_STAGE;
                    mbar_wait(bars + BAR_EMPTYA + 8 * st, ((g >> 2) - 1) & 1);
                    H3_TR(1, 256 + g);
                    mbar_expect_tx(full, A_STAGE);
                    tma_2d(a, &p.tmXn128, k0, mrow1, full);
                    tma_3d_h(a + 16384, &p.tmWg2, 0, k0, ng, full, pol);
                    tma_3d_h(a + 32768, &p.tmWu2, 0, k0, ng, full, pol);
                    if (g == 3 * ((cta & 31) >> 2) - 2) { pf_bulk_h(p.k + (size_t)cta * 16 * D, 32768, pol); pf_bulk_h(p.v + (size_t)cta * 16 * D, 32768, pol); }
                    const int G = g + 8;
                    if (G < 48) {
                        if ((G & 15) == m1) { const int pg_ = ((G >> 4) * 8 + nb1) * 2; pf_3d_h(&p.tmWg2, 0, m1 * 64, pg_, pol); pf_3d_h(&p.tmWu2, 0, m1 * 64, pg_, pol); }
                    } else if (G - 48 == m2 || G - 40 == m2) {
                        pf_3d_h(&p.tmWg1, 0, m2 * 64, ngh, pol); pf_3d_h(&p.tmWu1, 0, m2 * 64, ngh, pol);
                    }
                }
                cluster_wait();
                flag_wait(p.flags + (FL_XN + m2) * FLAG_STRIDE, 64);
                pf_bulk_h(p.ssm_k + (size_t)cta * 8 * S, 32768, pol);
                int st = 0; uint32_t ph = 1;
#pragma unroll 1
                for (int e = 0; e < 16; e++) {
                    const uint32_t full = bars + BAR_FULLB + 8 * st, a = sb + st * B_STAGE;
                    if (e < 6) {
                        if (e != 2 && e != 5) mbar_wait(bars + BAR_FINALA + 8 * (e - (e >= 3)), 0);
                    } else {
                        mbar_wait(bars + BAR_EMPTYB + 8 * st, ph);
                    }
                    H3_TR(1, 304 + e);
                    mbar_expect_tx(full, B_STAGE);
                    tma_2d_mc(a + rank * 8192, &p.tmXn64, e * 64, mrow2, full);
                    tma_3d_h(a + 16384, &p.tmWg1, 0, e * 64, ngh, full, pol);
                    tma_3d_h(a + 24576, &p.tmWu1, 0, e * 64, ngh, full, pol);
                    if (++st == 6) { st = 0; ph ^= 1; }
                }
                mbar_wait(bars + BAR_EMPTYB + 8 * ST_H, 1);
                mbar_expect_tx(bars + BAR_FULLB + 8 * ST_H, 32768);
                bulk_g2s_h(sb + ST_H * B_STAGE, p.ssm_k + (size_t)cta * 8 * S, 32768, bars + BAR_FULLB + 8 * ST_H, pol);
                unsigned kv_ready;
                asm volatile("ld.acquire.gpu.global.u32 %0, [%1];" : "=r"(kv_ready) : "l"(p.flags + FL_KV * FLAG_STRIDE) : "memory");
#pragma unroll 1
                for (int pass = 0; pass < 2; pass++) {
                    if ((pass == 0) == (kv_ready >= 4)) {
                        mbar_wait(bars + BAR_EMPTYB + 8 * ST_U, 1);
                        flag_wait(p.flags + FL_KV * FLAG_STRIDE, 4);
                        mbar_expect_tx(bars + BAR_FULLB + 8 * ST_U, 32768);
#pragma unroll 1
                        for (int ch = 0; ch < 8; ch++) bulk_g2s_h(sb + ST_U * B_STAGE + ch * U_PITCH, p.kvT + (size_t)(cta * 8 + ch) * S, 4096, bars + BAR_FULLB + 8 * ST_U, pol);
                    }
                    if (pass == 0) {
#pragma unroll 1
                        for (int c = 0; c < 4; c++) { mbar_wait(bars + BAR_EMPTYB + 8 * c, 0); mbar_arrive(bars + BAR_FULLB + 8 * c); }
                    }
                }
#pragma unroll 1
                for (int kb = m2; kb < 56; kb += 16) pf_3d(&p.tmWd, 0, kb * 64, n2 >> 6);
                flag_wait(p.flags + (FL_H + m2) * FLAG_STRIDE, 16);
#pragma unroll 1
                for (int kb = (pair & 3) * 2 + (int)rank; kb < 32; kb += 8) { pf_2d(&p.tmH64, kb * 64, m2 * 128); pf_2d(&p.tmH64, kb * 64, m2 * 128 + 64); }
                H3_STAMP(2);
                int i6 = 0; uint32_t rho = 0;
#pragma unroll 1
                for (int kb = 0; kb < 56; kb++) {
                    const int sg = (0x541023 >> (4 * i6)) & 15;
                    const uint32_t par = ((0x30u >> i6) & 1u) ^ rho;
                    const uint32_t full = bars + BAR_FULLB + 8 * sg, a = sb + sg * B_STAGE;
                    mbar_wait(bars + BAR_EMPTYB + 8 * sg, par ^ 1);
                    if (kb == 32) flag_wait(p.flags + (FL_H2 + m2) * FLAG_STRIDE, 16);
                    H3_TR(2, 256 + kb);
                    mbar_expect_tx(full, B_STAGE);
                    tma_2d_mc(a + rank * 8192, &p.tmH64, kb * 64, mrow2, full);
                    tma_3d(a + 16384, &p.tmWd, 0, kb * 64, n2 >> 6, full);
                    if (kb == 36) {
                        flag_wait(p.flags + (FL_Y + (n2 >> 7)) * FLAG_STRIDE, 128);
                        mbar_wait(bars + BAR_STGEMPTY, 0);
                        mbar_expect_tx(bars + BAR_OPFULL, 32768);
                        tma_2d(sb + OFF_STG, &p.tmY2T, 1984 - m2 * 128, n2, bars + BAR_OPFULL);
                        tma_2d(sb + OFF_STG + 16384, &p.tmY2T, 1920 - m2 * 128, n2, bars + BAR_OPFULL);
                    }
                    if (kb == 30) { pf_2d(&p.tmX128, n2, m2 * 128); pf_2d(&p.tmX128, n2 + 64, m2 * 128); }
                    if (++i6 == 6) { i6 = 0; rho ^= 1; }
                }
                mbar_wait(bars + BAR_EMPTYB + 0, 0);
                mbar_expect_tx(bars + BAR_FULLB + 0, 32768);
                tma_2d(sb, &p.tmX128, n2, m2 * 128, bars + BAR_FULLB + 0);
                tma_2d(sb + 16384, &p.tmX128, n2 + 64, m2 * 128, bars + BAR_FULLB + 0);
                unsigned old;
                asm volatile("atom.acq_rel.gpu.global.add.u32 %0, [%1], 1;" : "=r"(old) : "l"(p.flags + FL_DONE * FLAG_STRIDE) : "memory");
                if (old == NCTA - 1) {
#pragma unroll 1
                    for (int i = 0; i < FL_COUNT; i++) p.flags[i * FLAG_STRIDE] = 0;
                }
            } else {
                cluster_wait();
            }
        } else {
            if (tid == 32) H3_GSTAMP(30);
            cluster_wait();
            const int wt = tid - 32;
#pragma unroll 1
            for (int Ri = 0; Ri < 7; Ri++) {
                const int R = (Ri == 5) ? 6 : (Ri == 6) ? 5 : Ri;
                const uint32_t buf = (R == 4) ? sb + ST_ALT2 * B_STAGE : (R == 6) ? sb + ST_ALT * B_STAGE : sb + OFF_STG;
                mbar_wait(bars + ((R == 4) ? BAR_ALT2FULL : (R == 6) ? BAR_ALTFULL : BAR_STGFULL), (R < 4) ? (R & 1) : 0);
                if (wt == 0) H3_TR(3, 200 + R * 4);
#pragma unroll 1
                for (int i0 = wt; i0 < 1024; i0 += 2 * 96) {
                    const int i1 = i0 + 96;
                    const uint32_t a0 = buf + (i0 >> 9) * 16384 + (i0 & 511) * 16;
                    const uint32_t a1 = (i1 < 1024) ? buf + (i1 >> 9) * 16384 + (i1 & 511) * 16 : a0;
                    uint4 g0 = lds128(a0), u0 = lds128(a0 + 8192), g1 = lds128(a1), u1 = lds128(a1 + 8192);
                    g0.x = bf2_mul(silu_bf2(g0.x), u0.x); g0.y = bf2_mul(silu_bf2(g0.y), u0.y); g0.z = bf2_mul(silu_bf2(g0.z), u0.z); g0.w = bf2_mul(silu_bf2(g0.w), u0.w);
                    g1.x = bf2_mul(silu_bf2(g1.x), u1.x); g1.y = bf2_mul(silu_bf2(g1.y), u1.y); g1.z = bf2_mul(silu_bf2(g1.z), u1.z); g1.w = bf2_mul(silu_bf2(g1.w), u1.w);
                    sts128(a0, g0.x, g0.y, g0.z, g0.w);
                    if (i1 < 1024) sts128(a1, g1.x, g1.y, g1.z, g1.w);
                }
                if (wt == 0) H3_TR(3, 200 + R * 4 + 1);
                fence_async_smem();
                bar_sync(4, 96);
                if (wt == 0) {
                    const int mm = (R < 6) ? m1 : m2;
                    const int col = (R < 6) ? (8 * (R >> 1) + nb1) * 128 + (R & 1) * 64 : nh * 128 + (int)rank * 64;
                    tma_store_2d(&p.tmH64, buf, col, mm * 128);
                    tma_store_2d(&p.tmH64, buf + 16384, col, mm * 128 + 64);
                    bulk_commit();
                    bulk_wait_read();
                    if (R != 4 && R != 6) mbar_arrive(bars + BAR_STGEMPTY);
                    else {
                        const uint32_t eb = bars + BAR_EMPTYB + 8 * ((R == 4) ? ST_ALT2 : ST_ALT);
                        mbar_arrive_cta(eb, 0); mbar_arrive_cta(eb, 0); mbar_arrive_cta(eb, 1); mbar_arrive_cta(eb, 1);
                    }
                    H3_TR(3, 200 + R * 4 + 2);
                    if (R == 1 || R == 3 || R >= 5) {
                        bulk_wait_all();
                        flag_add_after_bulk(p.flags + ((R < 4 ? FL_H : FL_H2) + mm) * FLAG_STRIDE);
                    }
                }
            }
        }
        __syncwarp();
        cluster_sync();
    } else {
        asm volatile("setmaxnreg.inc.sync.aligned.u32 224;\n");
        const int cw = wg - 1;
        const int w = (tid >> 5) & 3;
        const int wtid = tid & 127;

        {
            const int rl = (cw * 4 + w) * 2 + (lane >> 4);
            const uint32_t src = sb + OFF_STG + rl * 2048 + (lane & 15) * 16;
            if (tid == 128) H3_STAMP(15);
            float s0 = 0.f, s1 = 0.f, s2 = 0.f, s3 = 0.f;
#pragma unroll
            for (int i = 0; i < 32; i += 2) { s0 += bf_lo(x[i]); s1 += bf_hi(x[i]); s2 += bf_lo(x[i + 1]); s3 += bf_hi(x[i + 1]); }
            float s = (s0 + s1) + (s2 + s3);
#pragma unroll
            for (int o = 8; o > 0; o >>= 1) s += __shfl_xor_sync(0xffffffffu, s, o);
            const float mu = s * (1.0f / D);
            s0 = s1 = s2 = s3 = 0.f;
#pragma unroll
            for (int i = 0; i < 32; i += 2) {
                const float a = bf_lo(x[i]) - mu, b = bf_hi(x[i]) - mu, c = bf_lo(x[i + 1]) - mu, d = bf_hi(x[i + 1]) - mu;
                s0 = fmaf(a, a, s0); s1 = fmaf(b, b, s1); s2 = fmaf(c, c, s2); s3 = fmaf(d, d, s3);
            }
            float v = (s0 + s1) + (s2 + s3);
#pragma unroll
            for (int o = 8; o > 0; o >>= 1) v += __shfl_xor_sync(0xffffffffu, v, o);
            if (tid == 128) H3_STAMP(17);
            const uint32_t mu2 = pack_bf2(mu, mu);
            const float vb = bf_lo(pack_bf2(v * (1.0f / D), 0.f));
            const float ve = bf_lo(pack_bf2(vb + 1e-5f, 0.f));
            const float sd = bf_lo(pack_bf2(sqrtf(ve), 0.f));
            const float inv = __frcp_rn(sd);
#pragma unroll
            for (int i = 0; i < 8; i++) {
                uint32_t oo[4];
#pragma unroll
                for (int e = 0; e < 4; e++) { const uint32_t dd = bf2_sub(x[4 * i + e], mu2); oo[e] = pack_bf2(bf_lo(dd) * inv, bf_hi(dd) * inv); }
                sts128(src + i * 256, oo[0], oo[1], oo[2], oo[3]);
            }
            if ((lane & 15) == 0) asm volatile("st.shared.v2.b32 [%0], {%1, %2};" :: "r"(bars + OFF_STAT + rl * 8), "r"(mu2), "r"(__float_as_uint(inv)) : "memory");
            fence_async_smem();
            __syncwarp();
            if (tid == 128) H3_STAMP(18);
            if (lane == 0) {
                bulk_s2g(p.xn + (size_t)(cta * 16 + (cw * 4 + w) * 2) * D, sb + OFF_STG + (cw * 4 + w) * 4096, 4096);
                bulk_s2g(p.stats + cta * 16 + (cw * 4 + w) * 2, bars + OFF_STAT + (cw * 4 + w) * 16, 16);
                bulk_commit();
                bulk_wait_all();
                flag_add_after_bulk(p.flags + (FL_XN + (cta >> 3)) * FLAG_STRIDE);
            }
            if (tid == 128) H3_STAMP(19);
            bar_sync(3, 256);
        }
        if (tid == 128) H3_STAMP(3);
        cluster_wait();

        const uint32_t lrow = w * 16 + (lane & 7) + ((lane >> 3) & 1) * 8;
        const uint32_t lrow7 = lane & 7;
        const uint32_t lgrp = lane >> 4;
        const uint32_t stg_lane = sb + OFF_STG + cw * 16384 + lrow * 128;
        const uint64_t descA = make_desc(sb + cw * 8192, 16, 1024);
        const uint64_t descB = make_desc(sb + 16384, 8192, 1024);

        int st = 0; uint32_t ph = 0;
        uint32_t pg[32], pu[32], qg[16], qu[16];
        {
            float acc[128];
            int prev = 0;
#pragma unroll 1
            for (int g = 0; g < 64; g++) {
                const int kb = g & 15;
                if (g < 48) {
                    const int sa = g & 3;
                    mbar_wait(bars + BAR_FULLA + 8 * sa, (g >> 2) & 1);
                    if (g == 0 && tid == 128) H3_STAMP(4);
                    if (wtid == 0) H3_TR(1, cw * 128 + g * 2);
                    const uint64_t da = descA + sa * (A_STAGE >> 4), db = descB + sa * (A_STAGE >> 4);
                    wg_fence();
                    wgmma_256(acc, da, db, kb != 0);
#pragma unroll
                    for (int k = 1; k < 4; k++) wgmma_256(acc, da + k * 2, db + k * 128, 1);
                    wg_commit();
                } else {
                    mbar_wait(bars + BAR_FULLB + 8 * st, ph);
                    if (wtid == 0) H3_TR(1, cw * 128 + g * 2);
                    const uint64_t da = descA + st * (B_STAGE >> 4), db = descB + st * (B_STAGE >> 4);
                    wg_fence();
                    wgmma_128_lo(acc, da, db, kb != 0);
#pragma unroll
                    for (int k = 1; k < 4; k++) wgmma_128_lo(acc, da + k * 2, db + k * 128, 1);
                    wg_commit();
                }
                wg_wait<1>();
                if (wtid == 0) H3_TR(1, cw * 128 + g * 2 + 1);
                if (kb > 0) {
                    if (g > 48) { if (wtid < 2) mbar_arrive_cta(bars + BAR_EMPTYB + 8 * prev, wtid); }
                    else if (g > 44) { if (wtid < 2) mbar_arrive_cta(bars + BAR_FINALA + 8 * (g - 45), wtid); }
                    else if (wtid == 0) mbar_arrive(bars + BAR_EMPTYA + 8 * ((g - 1) & 3));
                }
                if (g >= 48) { prev = st; if (++st == 6) { st = 0; ph ^= 1; } }
                if (g >= 16 && g < 48) {
                    const int pc = (kb < 4) ? kb : ((kb >= 9 && kb < 13) ? kb - 5 : -1);
                    if (pc >= 0) {
                        if (pc == 0 && g >= 32) mbar_wait(bars + BAR_STGEMPTY, 1);
                        if (pc == 4) mbar_wait(bars + BAR_STGEMPTY, 0);
                        stage_piece_dyn(pc, pg, pu, stg_lane, lrow7, lgrp);
                        if ((pc & 3) == 3) { __syncwarp(); if (lane == 0) mbar_arrive(bars + BAR_STGFULL); }
                    }
                }
                if (kb == 15 && g < 48) {
                    wg_wait<0>();
                    if (wtid == 0) H3_TR(1, 330 + cw * 16 + (g >> 4) * 2);
                    if (g == 47) { if (wtid < 2) mbar_arrive_cta(bars + BAR_FINALA + 24, wtid); }
                    else if (wtid == 0) mbar_arrive(bars + BAR_EMPTYA + 24);
#pragma unroll
                    for (int i = 0; i < 32; i++) { pg[i] = pack_bf2(acc[2 * i], acc[2 * i + 1]); pu[i] = pack_bf2(acc[64 + 2 * i], acc[64 + 2 * i + 1]); }
                    if (wtid == 0) H3_TR(1, 330 + cw * 16 + (g >> 4) * 2 + 1);
                    if (tid == 128) H3_STAMP(5 + (g >> 4));
                }
            }
            wg_wait<0>();
            if (wtid < 2) mbar_arrive_cta(bars + BAR_EMPTYB + 8 * prev, wtid);
#pragma unroll
            for (int i = 0; i < 16; i++) { qg[i] = pack_bf2(acc[2 * i], acc[2 * i + 1]); qu[i] = pack_bf2(acc[32 + 2 * i], acc[32 + 2 * i + 1]); }
            if (tid == 128) H3_STAMP(14);
        }
        mbar_wait(bars + BAR_FULLB + 8 * ST_ALT2, 1);
        {
            const uint32_t alt_lane = sb + ST_ALT2 * B_STAGE + cw * 16384 + lrow * 128;
            stage_piece<0>(pg, pu, alt_lane, lrow7, lgrp); stage_piece<1>(pg, pu, alt_lane, lrow7, lgrp);
            stage_piece<2>(pg, pu, alt_lane, lrow7, lgrp); stage_piece<3>(pg, pu, alt_lane, lrow7, lgrp);
            __syncwarp(); if (lane == 0) mbar_arrive(bars + BAR_ALT2FULL);
        }
        mbar_wait(bars + BAR_STGEMPTY, 1);
        stage_piece<4>(pg, pu, stg_lane, lrow7, lgrp); stage_piece<5>(pg, pu, stg_lane, lrow7, lgrp);
        stage_piece<6>(pg, pu, stg_lane, lrow7, lgrp); stage_piece<7>(pg, pu, stg_lane, lrow7, lgrp);
        __syncwarp(); if (lane == 0) mbar_arrive(bars + BAR_STGFULL);
        mbar_wait(bars + BAR_FULLB + 8 * ST_ALT, 1);
        {
            const uint32_t alt_lane = sb + ST_ALT * B_STAGE + cw * 16384 + lrow * 128;
#pragma unroll
            for (int i = 0; i < 4; i++) {
                const uint32_t addr = alt_lane + (((2 * i + lgrp) ^ lrow7) << 4);
                stsm_x4(addr, qg[4 * i], qg[4 * i + 1], qg[4 * i + 2], qg[4 * i + 3]);
                stsm_x4(addr + 8192, qu[4 * i], qu[4 * i + 1], qu[4 * i + 2], qu[4 * i + 3]);
            }
            __syncwarp(); if (lane == 0) mbar_arrive(bars + BAR_ALTFULL);
        }
        if (tid == 128) H3_STAMP(8);
        {
            const int r = lane >> 2, c4 = lane & 3;
            if (lane == 0) H3_TR(3, (cw * 4 + w) * 16 + 0);
            mbar_wait(bars + BAR_FULLB + 8 * ST_H, 0);
            mbar_wait(bars + BAR_FULLB + 8 * ST_C0, 1);
            mbar_wait(bars + BAR_FULLB + 8 * ST_C1, 1);
            if (tid == 128) H3_STAMP(23);
            {
                const uint32_t sH = sb + ST_H * B_STAGE + (cw * 4 + w) * 4096;
                const uint32_t sA = sb + (w >> 1) * B_STAGE + ((w & 1) * 2 + cw) * 8192, sB = sA + 4096;
                uint4 hv[8]; uint32_t hp[8];
#pragma unroll
                for (int i = 0; i < 8; i++) {
                    const int Q = i * 32 + lane;
                    hv[i] = lds128(sH + (255 - Q) * 16);
                    hp[i] = lds32(sH + (254 - Q) * 16 + 12);
                }
                if (lane == 31) hp[7] = 0;
#pragma unroll
                for (int i = 0; i < 8; i++) {
                    const int Q = i * 32 + lane;
                    const uint4 a = hv[i];
                    const uint32_t prev = hp[i];
                    sts128(sA + Q * 16, __byte_perm(a.w, 0, 0x1032), __byte_perm(a.z, 0, 0x1032), __byte_perm(a.y, 0, 0x1032), __byte_perm(a.x, 0, 0x1032));
                    sts128(sB + (Q ^ 2) * 16, __byte_perm(a.w, a.z, 0x7610), __byte_perm(a.z, a.y, 0x7610), __byte_perm(a.y, a.x, 0x7610), __byte_perm(a.x, prev, 0x7610));
                }
            }
            if (tid == 128) H3_STAMP(24);
            mbar_wait(bars + BAR_FULLB + 8 * ST_U, 0);
            if (tid == 128) H3_STAMP(25);
            if (lane == 0) sts128(sb + ST_U * B_STAGE + (cw * 4 + w) * U_PITCH + 4096, 0, 0, 0, 0);
            fence_async_smem();
            bar_sync(3, 256);
            const uint32_t red = sb + ST_H * B_STAGE;
            const uint32_t rx = 8 * (r & 3);
            if (cw == 0 && c4 < w) sts64f_o<0>(red + w * 8192 + r * 1024 + (((2 * c4) ^ rx) << 2), 0.f, 0.f);
            if (cw == 1) bar_arrive(5, 256);
            if (tid == 128) H3_STAMP(9);
            const bool useA = (r & 1);
            const int wl = (useA ? (2047 - r + 2 * c4) / 2 : (2046 - r + 2 * c4) / 2) - 8 * w;
            const uint32_t xorm = useA ? 0u : 8u;
            const int y0 = r - 2 * c4;
            const uint32_t mask0 = (w == 0) ? ((y0 >= 0 ? 0x0000FFFFu : 0u) | (y0 >= 1 ? 0xFFFF0000u : 0u)) : 0xFFFFFFFFu;
            uint32_t a[16][4];
            {
                const uint32_t hb = sb + cw * 8192 + (useA ? 0u : 4096u);
                conv_load_a<0>(a, hb + (((uint32_t)wl ^ xorm) << 2), hb + (((uint32_t)(wl - 4) ^ xorm) << 2));
                a[0][0] &= mask0;
            }
#pragma unroll 1
            for (int ci = 0; ci < 4; ci++) {
                const int ch = cw * 4 + ci, k = 2 * ci + cw;
                if (lane == 0) H3_TR(3, (cw * 4 + w) * 16 + 1 + ci * 3);
                const uint32_t sU = sb + ST_U * B_STAGE + ch * U_PITCH;
                const unsigned short dsc = __ldg(reinterpret_cast<const unsigned short*>(p.ssm_D) + cta * 8 + ch);
                float acc[128];
                bar_sync(5 + cw, 256);
                wg_fence();
                conv_issue<0>(acc, a, make_desc_noswz(sU, 16, 128));
                wg_commit();
                if (k < 7) bar_arrive(5 + (cw ^ 1), 256);
                wg_wait<0>();
                if ((ci & 1) && wtid < 2) mbar_arrive_cta(bars + BAR_EMPTYB + 8 * (ci >> 1), wtid);
                if (lane == 0) H3_TR(3, (cw * 4 + w) * 16 + 2 + ci * 3);
                if (k > 0) mbar_wait(bars + BAR_REDFREE, (k - 1) & 1);
                {
                    uint32_t wb[4];
#pragma unroll
                    for (int g = 0; g < 4; g++) wb[g] = red + w * 8192 + r * 1024 + ((((uint32_t)(254 - 2 * c4 + 2 * w - 8 * g)) ^ rx) << 2);
                    conv_store_part<0>(acc, wb, c4 >= w);
                }
                if (ci < 3) {
                    const uint32_t hb = sb + ((ci + 1) >> 1) * B_STAGE + (((ci + 1) & 1) * 2 + cw) * 8192 + (useA ? 0u : 4096u);
                    conv_load_a<0>(a, hb + (((uint32_t)wl ^ xorm) << 2), hb + (((uint32_t)(wl - 4) ^ xorm) << 2));
                    a[0][0] &= mask0;
                }
                if (lane == 0 && ci == 1) H3_TR(3, (cw * 4 + w) * 16 + 13);
                bar_sync(1 + cw, 128);
                if (lane == 0 && ci == 1) H3_TR(3, (cw * 4 + w) * 16 + 14);
                float z[16];
#pragma unroll
                for (int g = 0; g < 4; g++) {
                    const uint32_t rb = red + r * 1024 + ((((uint32_t)(254 - 2 * c4 - 8 * g - 64 * w)) ^ rx) << 2);
                    float2 t0 = lds64f_o<0>(rb), t1 = lds64f_o<8192>(rb), t2 = lds64f_o<16384>(rb), t3 = lds64f_o<24576>(rb);
                    float2 t4 = lds64f_o<-128>(rb), t5 = lds64f_o<8192 - 128>(rb), t6 = lds64f_o<16384 - 128>(rb), t7 = lds64f_o<24576 - 128>(rb);
                    z[2 * g] = (t0.y + t1.y) + (t2.y + t3.y); z[2 * g + 1] = (t0.x + t1.x) + (t2.x + t3.x);
                    z[8 + 2 * g] = (t4.y + t5.y) + (t6.y + t7.y); z[8 + 2 * g + 1] = (t4.x + t5.x) + (t6.x + t7.x);
                }
                __syncwarp();
                if (lane == 0 && ci == 1) H3_TR(3, (cw * 4 + w) * 16 + 15);
                if (lane == 0) mbar_arrive(bars + BAR_REDFREE);
                {
                    const uint32_t d2 = (uint32_t)dsc | ((uint32_t)dsc << 16);
#pragma unroll
                    for (int i = 0; i < 2; i++) {
                        const uint32_t ua = sU + (64 * w + 32 * i + lane) * 16;
                        uint32_t k0, k1, k2, k3;
                        ldsm_x4_t(ua, k0, k1, k2, k3);
                        stsm_x4_t(ua, bf2_add(pack_bf2(z[8 * i + 0], z[8 * i + 1]), bf2_mul(k0, d2)), bf2_add(pack_bf2(z[8 * i + 2], z[8 * i + 3]), bf2_mul(k1, d2)),
                                  bf2_add(pack_bf2(z[8 * i + 4], z[8 * i + 5]), bf2_mul(k2, d2)), bf2_add(pack_bf2(z[8 * i + 6], z[8 * i + 7]), bf2_mul(k3, d2)));
                    }
                }
                if (ci == 3) { bar_sync(1 + cw, 128); if (wtid < 2) mbar_arrive_cta(bars + BAR_EMPTYB + 8 * ST_H, wtid); }
                fence_async_smem();
                __syncwarp();
                if (lane == 0) { bulk_s2g(p.y2T + (size_t)(cta * 8 + ch) * S + w * 512, sU + w * 1024, 1024); bulk_commit(); }
                if (lane == 0) H3_TR(3, (cw * 4 + w) * 16 + 3 + ci * 3);
            }
            if (lane == 0) bulk_wait_read();
            bar_sync(1 + cw, 128);
            if (wtid < 2) mbar_arrive_cta(bars + BAR_EMPTYB + 8 * ST_U, wtid);
            if (tid == 128) H3_STAMP(11);
        }
        {
            float acc[64];
            uint2 st0, st1;
            int i6 = 0, prev = 0; uint32_t rho = 0;
#pragma unroll 1
            for (int kb = 0; kb < 56; kb++) {
                const int sg = (0x541023 >> (4 * i6)) & 15;
                mbar_wait(bars + BAR_FULLB + 8 * sg, ((0x30u >> i6) & 1u) ^ rho);
                if (wtid == 0) H3_TR(2, cw * 128 + kb * 2);
                const uint64_t da = descA + sg * (B_STAGE >> 4), db = descB + sg * (B_STAGE >> 4);
                wg_fence();
                wgmma_128(acc, da, db, kb != 0);
#pragma unroll
                for (int k = 1; k < 4; k++) wgmma_128(acc, da + k * 2, db + k * 128, 1);
                wg_commit();
                if (kb == 2 && lane == 0) { bulk_wait_all(); flag_add_after_bulk(p.flags + (FL_Y + (cta >> 4)) * FLAG_STRIDE); }
                if (kb == 44) {
                    const int row = m2 * 128 + cw * 64 + w * 16 + (lane >> 2);
                    st0 = __ldcg(p.stats + row); st1 = __ldcg(p.stats + row + 8);
                }
                wg_wait<1>();
                if (wtid == 0) H3_TR(2, cw * 128 + kb * 2 + 1);
                if (kb > 0 && wtid < 2) mbar_arrive_cta(bars + BAR_EMPTYB + 8 * prev, wtid);
                prev = sg;
                if (++i6 == 6) { i6 = 0; rho ^= 1; }
            }
            mbar_wait(bars + BAR_OPFULL, 0);
            wg_wait<0>();
            if (tid == 128) H3_STAMP(12);
            mbar_wait(bars + BAR_FULLB + 0, 1);
            if (tid == 128) H3_STAMP(20);
            const float inv0 = __uint_as_float(st0.y), inv1 = __uint_as_float(st1.y);
            const uint32_t ycol = sb + OFF_STG + cw * 16384 + (((7 - 2 * w - ((lane >> 3) & 1)) ^ lrow7) << 4) + lrow7 * 128;
            const uint32_t xrow = sb + (cw * 64 + lrow) * 128;
#pragma unroll 1
            for (int g2 = 0; g2 < 4; g2++) {
#pragma unroll
                for (int hh = 0; hh < 2; hh++) {
                    const uint32_t grp = g2 * 4 + hh * 2 + lgrp;
                    const uint32_t xa = xrow + (grp >> 3) * 16384 + (((grp & 7) ^ lrow7) << 4);
                    uint32_t x[4], y[4], o[4];
                    ldsm_x4(xa, x[0], x[1], x[2], x[3]);
                    ldsm_x4_t(ycol + grp * 1024, y[0], y[1], y[2], y[3]);
#pragma unroll
                    for (int i = 0; i < 4; i++) {
                        const uint32_t dd = bf2_sub(x[i], (i & 1) ? st1.x : st0.x);
                        const float iv = (i & 1) ? inv1 : inv0;
                        const uint32_t xn = pack_bf2(bf_lo(dd) * iv, bf_hi(dd) * iv);
                        o[i] = bf2_add(x[i], bf2_mul(bf2_mul(xn, y[i]), silu_bf2(pack_bf2(acc[8 * hh + 2 * i], acc[8 * hh + 2 * i + 1]))));
                    }
                    stsm_x4(xa, o[0], o[1], o[2], o[3]);
                }
#pragma unroll
                for (int i = 0; i < 48; i++) acc[i] = acc[i + 16];
            }
            if (tid == 128) H3_STAMP(21);
            fence_async_smem();
            bar_sync(1 + cw, 128);
            if (tid == 128) H3_STAMP(22);
            if (wtid == 0) {
                tma_store_2d(&p.tmOut64, sb + cw * 8192, n2, m2 * 128 + cw * 64);
                tma_store_2d(&p.tmOut64, sb + 16384 + cw * 8192, n2 + 64, m2 * 128 + cw * 64);
                bulk_commit();
                bulk_wait_all();
            }
            if (tid == 128) { H3_STAMP(13); H3_GSTAMP(31); }
        }
        cluster_sync();
    }
}

typedef CUresult (*EncodeTiledFn)(CUtensorMap*, CUtensorMapDataType, cuuint32_t, void*, const cuuint64_t*, const cuuint64_t*,
                                  const cuuint32_t*, const cuuint32_t*, CUtensorMapInterleave, CUtensorMapSwizzle,
                                  CUtensorMapL2promotion, CUtensorMapFloatOOBfill);

static void make_map(EncodeTiledFn enc, CUtensorMap* m, const void* ptr, int rank, const uint64_t* dims, const uint64_t* strides, const uint32_t* box,
                     CUtensorMapSwizzle swz = CU_TENSOR_MAP_SWIZZLE_128B) {
    cuuint64_t d[3], s[2];
    cuuint32_t b[3], es[3] = {1, 1, 1};
    for (int i = 0; i < rank; i++) { d[i] = dims[i]; b[i] = box[i]; }
    for (int i = 0; i + 1 < rank; i++) s[i] = strides[i];
    CUresult r = enc(m, CU_TENSOR_MAP_DATA_TYPE_BFLOAT16, rank, const_cast<void*>(ptr), d, s, b, es, CU_TENSOR_MAP_INTERLEAVE_NONE,
                     swz, CU_TENSOR_MAP_L2_PROMOTION_L2_128B, CU_TENSOR_MAP_FLOAT_OOB_FILL_NONE);
    if (r != CUDA_SUCCESS) fprintf(stderr, "cuTensorMapEncodeTiled failed: %d\n", (int)r);
}
static void map2d(EncodeTiledFn enc, CUtensorMap* m, const void* ptr, uint64_t cols, uint64_t rows, uint32_t box_rows) {
    const uint64_t d[2] = {cols, rows}, s[1] = {cols * 2};
    const uint32_t b[2] = {64, box_rows};
    make_map(enc, m, ptr, 2, d, s, b);
}
static void map3d(EncodeTiledFn enc, CUtensorMap* m, const void* ptr, uint64_t cols, uint64_t rows, uint32_t groups) {
    const uint64_t d[3] = {64, rows, cols / 64}, s[2] = {cols * 2, 128};
    const uint32_t b[3] = {64, 64, groups};
    make_map(enc, m, ptr, 3, d, s, b);
}

static long long* g_dbg_ptr = nullptr;

}

extern "C" void kernel_launch(void* const* d_in, const int* in_sizes, int n_in, void* d_out, int out_size) {
    using namespace h3;
    (void)in_sizes; (void)n_in; (void)out_size;
    static EncodeTiledFn enc = nullptr;
    static void *xn, *kvT, *hbuf, *y2T, *flags, *stats;
    if (!enc) {
        void* fn = nullptr;
        cudaDriverEntryPointQueryResult qr;
        cudaGetDriverEntryPoint("cuTensorMapEncodeTiled", &fn, cudaEnableDefault, &qr);
        enc = (EncodeTiledFn)fn;
        cudaGetSymbolAddress(&xn, g_xn);
        cudaGetSymbolAddress(&kvT, g_kvT);
        cudaGetSymbolAddress(&hbuf, g_h);
        cudaGetSymbolAddress(&y2T, g_y2T);
        cudaGetSymbolAddress(&flags, g_flags);
        cudaGetSymbolAddress(&stats, g_stats);
        cudaFuncSetAttribute(h3_kernel, cudaFuncAttributeMaxDynamicSharedMemorySize, SMEM_BYTES);
    }
    Params p;
    const bf16* q = (const bf16*)d_in[0];
    p.q = q; p.k = (const bf16*)d_in[1]; p.v = (const bf16*)d_in[2];
    p.shift_k = (const bf16*)d_in[3]; p.ssm_k = (const bf16*)d_in[4]; p.ssm_D = (const bf16*)d_in[5];
    const bf16* wg = (const bf16*)d_in[7];
    const bf16* wu = (const bf16*)d_in[8];
    const bf16* wd = (const bf16*)d_in[9];
    p.xn = (bf16*)xn; p.kvT = (bf16*)kvT; p.y2T = (bf16*)y2T; p.flags = (unsigned*)flags; p.stats = (uint2*)stats;
    p.dbg = g_dbg_ptr;
    map2d(enc, &p.tmXn128, xn, D, S, 128);
    map2d(enc, &p.tmXn64, xn, D, S, 64);
    map3d(enc, &p.tmWg2, wg, F, D, 2);
    map3d(enc, &p.tmWu2, wu, F, D, 2);
    map3d(enc, &p.tmWg1, wg, F, D, 1);
    map3d(enc, &p.tmWu1, wu, F, D, 1);
    map2d(enc, &p.tmH64, hbuf, F, S, 64);
    map3d(enc, &p.tmWd, wd, D, F, 2);
    map2d(enc, &p.tmX128, q, D, S, 128);
    map2d(enc, &p.tmY2T, y2T, S, D, 128);
    map2d(enc, &p.tmOut64, d_out, D, S, 64);
    {
        const uint64_t d[2] = {D, S}, st[1] = {D * 2};
        const uint32_t bk[2] = {128, 67}, bv[2] = {128, 64};
        make_map(enc, &p.tmK, p.k, 2, d, st, bk, CU_TENSOR_MAP_SWIZZLE_NONE);
        make_map(enc, &p.tmV, p.v, 2, d, st, bv, CU_TENSOR_MAP_SWIZZLE_NONE);
    }
    map2d(enc, &p.tmKvT, kvT, S, D, 128);

    cudaLaunchConfig_t cfg = {};
    cfg.gridDim = dim3(NCTA + 4);
    cfg.blockDim = dim3(384);
    cfg.dynamicSmemBytes = SMEM_BYTES;
    cfg.stream = cudaStreamPerThread;
    cudaLaunchAttribute at[1];
    at[0].id = cudaLaunchAttributeClusterDimension;
    at[0].val.clusterDim.x = 2; at[0].val.clusterDim.y = 1; at[0].val.clusterDim.z = 1;
    cfg.attrs = at; cfg.numAttrs = 1;
    cudaLaunchKernelEx(&cfg, h3_kernel, p);
}
```

```cpp
#include <cuda_runtime.h>
#include <cuda_bf16.h>
#include <cuda.h>
#include <stdint.h>
#include <stdio.h>

namespace h3 {

typedef __nv_bfloat16 bf16;

constexpr int S = 2048;
constexpr int D = 1024;
constexpr int F = 3584;
constexpr int NCTA = 128;

__device__ __align__(1024) bf16 g_xn[S * D];
__device__ __align__(1024) bf16 g_kvT[D * S];
__device__ __align__(1024) bf16 g_h[S * F];
__device__ __align__(1024) bf16 g_y2T[D * S];
__device__ __align__(1024) uint2 g_stats[S];
constexpr int FLAG_STRIDE = 32;
constexpr int FL_XN = 0, FL_H = 16, FL_Y = 32, FL_KV = 40, FL_DONE = 41, FL_H2 = 42, FL_COUNT = 58;
__device__ __align__(1024) unsigned g_flags[FL_COUNT * FLAG_STRIDE];

struct alignas(64) Params {
    CUtensorMap tmXn128;
    CUtensorMap tmXn64;
    CUtensorMap tmWg2;
    CUtensorMap tmWu2;
    CUtensorMap tmWg1;
    CUtensorMap tmWu1;
    CUtensorMap tmH64;
    CUtensorMap tmWd;
    CUtensorMap tmX128;
    CUtensorMap tmY2T;
    CUtensorMap tmOut64;
    CUtensorMap tmK;
    CUtensorMap tmV;
    CUtensorMap tmKvT;
    const bf16* q; const bf16* k; const bf16* v; const bf16* shift_k; const bf16* ssm_k; const bf16* ssm_D;
    bf16* xn; bf16* kvT; bf16* y2T; uint2* stats;
    unsigned* flags;
    long long* dbg;
};

constexpr uint32_t RING_BYTES = 196608;
constexpr uint32_t A_STAGE = 49152, B_STAGE = 32768;
constexpr uint32_t OFF_STG = RING_BYTES + 1024;
constexpr uint32_t OFF_BAR = OFF_STG + 32768;
constexpr uint32_t BAR_FULLA = 0, BAR_EMPTYA = 32, BAR_FULLB = 96, BAR_EMPTYB = 144,
                   BAR_STGFULL = 200, BAR_STGEMPTY = 208, BAR_ALTFULL = 216, BAR_OPFULL = 232,
                   BAR_ALT2FULL = 240, OFF_STAT = 256;
constexpr uint32_t SMEM_BYTES = OFF_BAR + 512 + 1024;

constexpr int ST_H = 4, ST_U = 5, ST_C0 = 0, ST_C1 = 1, ST_ALT = 2, ST_ALT2 = 3;
constexpr uint32_t U_PITCH = 4096 + 128;

__device__ __forceinline__ uint32_t smem_u32(const void* p) { return (uint32_t)__cvta_generic_to_shared(p); }
__device__ __forceinline__ uint64_t make_desc(uint32_t addr, uint32_t lbo, uint32_t sbo) {
    uint64_t d = (uint64_t)((addr & 0x3FFFF) >> 4);
    d |= (uint64_t)((lbo & 0x3FFFF) >> 4) << 16;
    d |= (uint64_t)((sbo & 0x3FFFF) >> 4) << 32;
    d |= (uint64_t)1 << 62;
    return d;
}
__device__ __forceinline__ uint64_t make_desc_noswz(uint32_t addr, uint32_t lbo, uint32_t sbo) {
    return (uint64_t)((addr & 0x3FFFF) >> 4) | ((uint64_t)(lbo >> 4) << 16) | ((uint64_t)(sbo >> 4) << 32);
}
constexpr uint32_t WAIT_LIMIT = 1u << 27;
__device__ __forceinline__ void mbar_init(uint32_t bar, uint32_t count) { asm volatile("mbarrier.init.shared::cta.b64 [%0], %1;" :: "r"(bar), "r"(count) : "memory"); }
__device__ __forceinline__ void mbar_expect_tx(uint32_t bar, uint32_t bytes) { asm volatile("mbarrier.arrive.expect_tx.shared::cta.b64 _, [%0], %1;" :: "r"(bar), "r"(bytes) : "memory"); }
__device__ __forceinline__ void mbar_arrive(uint32_t bar) { asm volatile("mbarrier.arrive.shared::cta.b64 _, [%0];" :: "r"(bar) : "memory"); }
__device__ __forceinline__ void mbar_arrive_cta(uint32_t bar, uint32_t cta) {
    asm volatile("{\n.reg .b32 ra;\nmapa.shared::cluster.u32 ra, %0, %1;\nmbarrier.arrive.shared::cluster.b64 _, [ra];\n}" :: "r"(bar), "r"(cta) : "memory");
}
__device__ __forceinline__ uint32_t mbar_try(uint32_t bar, uint32_t parity) {
    uint32_t ok;
    asm volatile("{\n.reg .pred p;\nmbarrier.try_wait.parity.shared::cta.b64 p, [%1], %2;\nselp.u32 %0, 1, 0, p;\n}" : "=r"(ok) : "r"(bar), "r"(parity) : "memory");
    return ok;
}
__device__ __forceinline__ void mbar_wait(uint32_t bar, uint32_t parity) {
    if (!mbar_try(bar, parity)) {
        const uint32_t t0 = (uint32_t)clock();
        while (!mbar_try(bar, parity) && (uint32_t)clock() - t0 < WAIT_LIMIT) {}
    }
}
__device__ __forceinline__ void mbar_wait_idle(uint32_t bar, uint32_t parity) {
    const uint32_t t0 = (uint32_t)clock();
    while (!mbar_try(bar, parity) && (uint32_t)clock() - t0 < WAIT_LIMIT) {
        __nanosleep(256);
    }
}
__device__ __forceinline__ void flag_wait(const unsigned* f, unsigned target) {
    const uint32_t t0 = (uint32_t)clock();
    unsigned v;
    do {
        asm volatile("ld.acquire.gpu.global.u32 %0, [%1];" : "=r"(v) : "l"(f) : "memory");
    } while (v < target && (uint32_t)clock() - t0 < WAIT_LIMIT);
}
__device__ __forceinline__ void flag_add_after_bulk(unsigned* f) {
    asm volatile("red.relaxed.gpu.global.add.u32 [%0], 1;" :: "l"(f) : "memory");
}
__device__ __forceinline__ void cluster_arrive() { asm volatile("barrier.cluster.arrive.relaxed;" ::: "memory"); }
__device__ __forceinline__ void cluster_wait() { asm volatile("barrier.cluster.wait.acquire;" ::: "memory"); }
__device__ __forceinline__ void tma_2d(uint32_t dst, const CUtensorMap* m, int c0, int c1, uint32_t bar) {
    asm volatile("cp.async.bulk.tensor.2d.shared::cluster.global.mbarrier::complete_tx::bytes [%0], [%1, {%3, %4}], [%2];"
        :: "r"(dst), "l"(m), "r"(bar), "r"(c0), "r"(c1) : "memory");
}
__device__ __forceinline__ void tma_2d_mc(uint32_t dst, const CUtensorMap* m, int c0, int c1, uint32_t bar) {
    asm volatile("cp.async.bulk.tensor.2d.shared::cluster.global.mbarrier::complete_tx::bytes.multicast::cluster [%0], [%1, {%3, %4}], [%2], %5;"
        :: "r"(dst), "l"(m), "r"(bar), "r"(c0), "r"(c1), "h"((uint16_t)3) : "memory");
}
__device__ __forceinline__ void tma_3d(uint32_t dst, const CUtensorMap* m, int c0, int c1, int c2, uint32_t bar) {
    asm volatile("cp.async.bulk.tensor.3d.shared::cluster.global.mbarrier::complete_tx::bytes [%0], [%1, {%3, %4, %5}], [%2];"
        :: "r"(dst), "l"(m), "r"(bar), "r"(c0), "r"(c1), "r"(c2) : "memory");
}
__device__ __forceinline__ uint64_t policy_evict_first() {
    uint64_t pol; asm volatile("createpolicy.fractional.L2::evict_first.b64 %0, 1.0;" : "=l"(pol)); return pol;
}
__device__ __forceinline__ void tma_3d_h(uint32_t dst, const CUtensorMap* m, int c0, int c1, int c2, uint32_t bar, uint64_t pol) {
    asm volatile("cp.async.bulk.tensor.3d.shared::cluster.global.mbarrier::complete_tx::bytes.L2::cache_hint [%0], [%1, {%3, %4, %5}], [%2], %6;"
        :: "r"(dst), "l"(m), "r"(bar), "r"(c0), "r"(c1), "r"(c2), "l"(pol) : "memory");
}
__device__ __forceinline__ void tma_2d_h(uint32_t dst, const CUtensorMap* m, int c0, int c1, uint32_t bar, uint64_t pol) {
    asm volatile("cp.async.bulk.tensor.2d.shared::cluster.global.mbarrier::complete_tx::bytes.L2::cache_hint [%0], [%1, {%3, %4}], [%2], %5;"
        :: "r"(dst), "l"(m), "r"(bar), "r"(c0), "r"(c1), "l"(pol) : "memory");
}
__device__ __forceinline__ void pf_bulk_h(const void* src, uint32_t bytes, uint64_t pol) {
    asm volatile("cp.async.bulk.prefetch.L2.global.L2::cache_hint [%0], %1, %2;" :: "l"(src), "r"(bytes), "l"(pol) : "memory");
}
__device__ __forceinline__ void tma_3d_mc_h(uint32_t dst, const CUtensorMap* m, int c0, int c1, int c2, uint32_t bar, uint64_t pol) {
    asm volatile("cp.async.bulk.tensor.3d.shared::cluster.global.mbarrier::complete_tx::bytes.multicast::cluster.L2::cache_hint [%0], [%1, {%3, %4, %5}], [%2], %6, %7;"
        :: "r"(dst), "l"(m), "r"(bar), "r"(c0), "r"(c1), "r"(c2), "h"((uint16_t)3), "l"(pol) : "memory");
}
__device__ __forceinline__ void bulk_g2s_h(uint32_t dst, const void* src, uint32_t bytes, uint32_t bar, uint64_t pol) {
    asm volatile("cp.async.bulk.shared::cluster.global.mbarrier::complete_tx::bytes.L2::cache_hint [%0], [%1], %2, [%3], %4;"
        :: "r"(dst), "l"(src), "r"(bytes), "r"(bar), "l"(pol) : "memory");
}
__device__ __forceinline__ void bulk_s2g(void* dst, uint32_t src, uint32_t bytes) {
    asm volatile("cp.async.bulk.global.shared::cta.bulk_group [%0], [%1], %2;" :: "l"(dst), "r"(src), "r"(bytes) : "memory");
}
__device__ __forceinline__ void tma_store_2d(const CUtensorMap* m, uint32_t src, int c0, int c1) {
    asm volatile("cp.async.bulk.tensor.2d.global.shared::cta.bulk_group [%0, {%2, %3}], [%1];"
        :: "l"(m), "r"(src), "r"(c0), "r"(c1) : "memory");
}
__device__ __forceinline__ void pf_2d(const CUtensorMap* m, int c0, int c1) {
    asm volatile("cp.async.bulk.prefetch.tensor.2d.L2.global.tile [%0, {%1, %2}];" :: "l"(m), "r"(c0), "r"(c1) : "memory");
}
__device__ __forceinline__ void pf_bulk(const void* src, uint32_t bytes) {
    asm volatile("cp.async.bulk.prefetch.L2.global [%0], %1;" :: "l"(src), "r"(bytes) : "memory");
}
__device__ __forceinline__ void bulk_commit() { asm volatile("cp.async.bulk.commit_group;" ::: "memory"); }
__device__ __forceinline__ void bulk_wait_read() { asm volatile("cp.async.bulk.wait_group.read 0;" ::: "memory"); }
__device__ __forceinline__ void bulk_wait_all() { asm volatile("cp.async.bulk.wait_group 0;" ::: "memory"); }
__device__ __forceinline__ void fence_async_smem() { asm volatile("fence.proxy.async.shared::cta;" ::: "memory"); }
__device__ __forceinline__ void bar_sync(int id, int n) { asm volatile("bar.sync %0, %1;" :: "r"(id), "r"(n) : "memory"); }
__device__ __forceinline__ void bar_arrive(int id, int n) { asm volatile("bar.arrive %0, %1;" :: "r"(id), "r"(n) : "memory"); }
__device__ __forceinline__ void cluster_sync() {
    asm volatile("barrier.cluster.arrive.release.aligned;" ::: "memory");
    asm volatile("barrier.cluster.wait.acquire.aligned;" ::: "memory");
}
__device__ __forceinline__ void wg_fence() { asm volatile("wgmma.fence.sync.aligned;" ::: "memory"); }
__device__ __forceinline__ void wg_commit() { asm volatile("wgmma.commit_group.sync.aligned;" ::: "memory"); }
template <int N> __device__ __forceinline__ void wg_wait() { asm volatile("wgmma.wait_group.sync.aligned %0;" :: "n"(N) : "memory"); }

#define H3_R4(b)  "+f"(d[b+0]), "+f"(d[b+1]), "+f"(d[b+2]), "+f"(d[b+3])
#define H3_R8(b)  H3_R4(b), H3_R4(b+4)
#define H3_R16(b) H3_R8(b), H3_R8(b+8)
#define H3_R32(b) H3_R16(b), H3_R16(b+16)
#define H3_R64(b) H3_R32(b), H3_R32(b+32)

__device__ __forceinline__ void wgmma_256(float (&d)[128], uint64_t a, uint64_t b, int scale_d) {
    asm volatile("{\n.reg .pred p;\nsetp.ne.b32 p, %130, 0;\n"
    "wgmma.mma_async.sync.aligned.m64n256k16.f32.bf16.bf16 "
    "{%0,%1,%2,%3,%4,%5,%6,%7,%8,%9,%10,%11,%12,%13,%14,%15,"
    "%16,%17,%18,%19,%20,%21,%22,%23,%24,%25,%26,%27,%28,%29,%30,%31,"
    "%32,%33,%34,%35,%36,%37,%38,%39,%40,%41,%42,%43,%44,%45,%46,%47,"
    "%48,%49,%50,%51,%52,%53,%54,%55,%56,%57,%58,%59,%60,%61,%62,%63,"
    "%64,%65,%66,%67,%68,%69,%70,%71,%72,%73,%74,%75,%76,%77,%78,%79,"
    "%80,%81,%82,%83,%84,%85,%86,%87,%88,%89,%90,%91,%92,%93,%94,%95,"
    "%96,%97,%98,%99,%100,%101,%102,%103,%104,%105,%106,%107,%108,%109,%110,%111,"
    "%112,%113,%114,%115,%116,%117,%118,%119,%120,%121,%122,%123,%124,%125,%126,%127},"
    "%128, %129, p, 1, 1, 0, 1;\n}\n"
    : H3_R64(0), H3_R64(64)
    : "l"(a), "l"(b), "r"(scale_d));
}
__device__ __forceinline__ void wgmma_128(float (&d)[64], uint64_t a, uint64_t b, int scale_d) {
    asm volatile("{\n.reg .pred p;\nsetp.ne.b32 p, %66, 0;\n"
    "wgmma.mma_async.sync.aligned.m64n128k16.f32.bf16.bf16 "
    "{%0,%1,%2,%3,%4,%5,%6,%7,%8,%9,%10,%11,%12,%13,%14,%15,"
    "%16,%17,%18,%19,%20,%21,%22,%23,%24,%25,%26,%27,%28,%29,%30,%31,"
    "%32,%33,%34,%35,%36,%37,%38,%39,%40,%41,%42,%43,%44,%45,%46,%47,"
    "%48,%49,%50,%51,%52,%53,%54,%55,%56,%57,%58,%59,%60,%61,%62,%63},"
    "%64, %65, p, 1, 1, 0, 1;\n}\n"
    : H3_R64(0)
    : "l"(a), "l"(b), "r"(scale_d));
}
__device__ __forceinline__ void ldsm_x4(uint32_t addr, uint32_t& r0, uint32_t& r1, uint32_t& r2, uint32_t& r3) {
    asm volatile("ldmatrix.sync.aligned.m8n8.x4.shared.b16 {%0,%1,%2,%3}, [%4];" : "=r"(r0), "=r"(r1), "=r"(r2), "=r"(r3) : "r"(addr) : "memory");
}
__device__ __forceinline__ void ldsm_x4_t(uint32_t addr, uint32_t& r0, uint32_t& r1, uint32_t& r2, uint32_t& r3) {
    asm volatile("ldmatrix.sync.aligned.m8n8.x4.trans.shared.b16 {%0,%1,%2,%3}, [%4];" : "=r"(r0), "=r"(r1), "=r"(r2), "=r"(r3) : "r"(addr) : "memory");
}
__device__ __forceinline__ void stsm_x4(uint32_t addr, uint32_t r0, uint32_t r1, uint32_t r2, uint32_t r3) {
    asm volatile("stmatrix.sync.aligned.m8n8.x4.shared.b16 [%0], {%1,%2,%3,%4};" :: "r"(addr), "r"(r0), "r"(r1), "r"(r2), "r"(r3) : "memory");
}
template <int OFF> __device__ __forceinline__ uint32_t lds32_o(uint32_t addr) { uint32_t v; asm volatile("ld.shared.b32 %0, [%1+%2];" : "=r"(v) : "r"(addr), "n"(OFF) : "memory"); return v; }
__device__ __forceinline__ uint32_t lds32(uint32_t addr) { uint32_t v; asm volatile("ld.shared.b32 %0, [%1];" : "=r"(v) : "r"(addr) : "memory"); return v; }
__device__ __forceinline__ uint4 lds128(uint32_t addr) { uint4 v; asm volatile("ld.shared.v4.b32 {%0,%1,%2,%3}, [%4];" : "=r"(v.x), "=r"(v.y), "=r"(v.z), "=r"(v.w) : "r"(addr) : "memory"); return v; }
__device__ __forceinline__ void sts128(uint32_t addr, uint32_t a, uint32_t b, uint32_t c, uint32_t d) { asm volatile("st.shared.v4.b32 [%0], {%1,%2,%3,%4};" :: "r"(addr), "r"(a), "r"(b), "r"(c), "r"(d) : "memory"); }

__device__ __forceinline__ uint32_t bf2_mul(uint32_t a, uint32_t b) { uint32_t r; asm("mul.rn.bf16x2 %0, %1, %2;" : "=r"(r) : "r"(a), "r"(b)); return r; }
__device__ __forceinline__ uint32_t bf2_add(uint32_t a, uint32_t b) { uint32_t r; asm("add.rn.bf16x2 %0, %1, %2;" : "=r"(r) : "r"(a), "r"(b)); return r; }
__device__ __forceinline__ uint32_t bf2_sub(uint32_t a, uint32_t b) { uint32_t r; asm("sub.rn.bf16x2 %0, %1, %2;" : "=r"(r) : "r"(a), "r"(b)); return r; }
__device__ __forceinline__ uint32_t pack_bf2(float lo, float hi) { uint32_t r; asm("cvt.rn.bf16x2.f32 %0, %1, %2;" : "=r"(r) : "f"(hi), "f"(lo)); return r; }
__device__ __forceinline__ float bf_lo(uint32_t v) { return __uint_as_float(v << 16); }
__device__ __forceinline__ float bf_hi(uint32_t v) { return __uint_as_float(v & 0xFFFF0000u); }
__device__ __forceinline__ float silu_f(float x) {
    float e, r;
    asm("ex2.approx.ftz.f32 %0, %1;" : "=f"(e) : "f"(x * -1.4426950408889634f));
    asm("rcp.approx.ftz.f32 %0, %1;" : "=f"(r) : "f"(1.0f + e));
    return x * r;
}
__device__ __forceinline__ uint32_t silu_bf2(uint32_t v) { return pack_bf2(silu_f(bf_lo(v)), silu_f(bf_hi(v))); }

#define H3_TR(ph, i) do {} while (0)
#define H3_STAMP(i) do {} while (0)
#define H3_GSTAMP(i) do {} while (0)

template <int I>
__device__ __forceinline__ void stage_piece(const uint32_t (&pg)[32], const uint32_t (&pu)[32], uint32_t stg_lane, uint32_t lrow7, uint32_t lgrp) {
    const uint32_t addr = stg_lane + (((2 * (I & 3) + lgrp) ^ lrow7) << 4);
    stsm_x4(addr, pg[4 * I], pg[4 * I + 1], pg[4 * I + 2], pg[4 * I + 3]);
    stsm_x4(addr + 8192, pu[4 * I], pu[4 * I + 1], pu[4 * I + 2], pu[4 * I + 3]);
}
__device__ __forceinline__ void stage_piece_dyn(int i, const uint32_t (&pg)[32], const uint32_t (&pu)[32], uint32_t stg_lane, uint32_t lrow7, uint32_t lgrp) {
    switch (i) {
        case 0: stage_piece<0>(pg, pu, stg_lane, lrow7, lgrp); break;
        case 1: stage_piece<1>(pg, pu, stg_lane, lrow7, lgrp); break;
        case 2: stage_piece<2>(pg, pu, stg_lane, lrow7, lgrp); break;
        case 3: stage_piece<3>(pg, pu, stg_lane, lrow7, lgrp); break;
        case 4: stage_piece<4>(pg, pu, stg_lane, lrow7, lgrp); break;
        case 5: stage_piece<5>(pg, pu, stg_lane, lrow7, lgrp); break;
        case 6: stage_piece<6>(pg, pu, stg_lane, lrow7, lgrp); break;
        default: stage_piece<7>(pg, pu, stg_lane, lrow7, lgrp); break;
    }
}
__device__ __forceinline__ void wgmma_128_lo(float (&d)[128], uint64_t a, uint64_t b, int scale_d) {
    asm volatile("{\n.reg .pred p;\nsetp.ne.b32 p, %66, 0;\n"
    "wgmma.mma_async.sync.aligned.m64n128k16.f32.bf16.bf16 "
    "{%0,%1,%2,%3,%4,%5,%6,%7,%8,%9,%10,%11,%12,%13,%14,%15,"
    "%16,%17,%18,%19,%20,%21,%22,%23,%24,%25,%26,%27,%28,%29,%30,%31,"
    "%32,%33,%34,%35,%36,%37,%38,%39,%40,%41,%42,%43,%44,%45,%46,%47,"
    "%48,%49,%50,%51,%52,%53,%54,%55,%56,%57,%58,%59,%60,%61,%62,%63},"
    "%64, %65, p, 1, 1, 0, 1;\n}\n"
    : H3_R64(0)
    : "l"(a), "l"(b), "r"(scale_d));
}

template <int N> __device__ __forceinline__ void wgmma_rs(float (&d)[128], const uint32_t (&a)[4], uint64_t b, int scale_d);
template <> __device__ __forceinline__ void wgmma_rs<64>(float (&d)[128], const uint32_t (&a)[4], uint64_t b, int scale_d) {
    asm volatile("{\n.reg .pred p;\nsetp.ne.b32 p, %37, 0;\nwgmma.mma_async.sync.aligned.m64n64k16.f32.bf16.bf16 {%0,%1,%2,%3,%4,%5,%6,%7,%8,%9,%10,%11,%12,%13,%14,%15,%16,%17,%18,%19,%20,%21,%22,%23,%24,%25,%26,%27,%28,%29,%30,%31}, {%32,%33,%34,%35}, %36, p, 1, 1, 0;\n}\n"
        : "+f"(d[0]), "+f"(d[1]), "+f"(d[2]), "+f"(d[3]), "+f"(d[4]), "+f"(d[5]), "+f"(d[6]), "+f"(d[7]), "+f"(d[8]), "+f"(d[9]), "+f"(d[10]), "+f"(d[11]), "+f"(d[12]), "+f"(d[13]), "+f"(d[14]), "+f"(d[15]), "+f"(d[16]), "+f"(d[17]), "+f"(d[18]), "+f"(d[19]), "+f"(d[20]), "+f"(d[21]), "+f"(d[22]), "+f"(d[23]), "+f"(d[24]), "+f"(d[25]), "+f"(d[26]), "+f"(d[27]), "+f"(d[28]), "+f"(d[29]), "+f"(d[30]), "+f"(d[31])
        : "r"(a[0]), "r"(a[1]), "r"(a[2]), "r"(a[3]), "l"(b), "r"(scale_d));
}
template <> __device__ __forceinline__ void wgmma_rs<128>(float (&d)[128], const uint32_t (&a)[4], uint64_t b, int scale_d) {
    asm volatile("{\n.reg .pred p;\nsetp.ne.b32 p, %69, 0;\nwgmma.mma_async.sync.aligned.m64n128k16.f32.bf16.bf16 {%0,%1,%2,%3,%4,%5,%6,%7,%8,%9,%10,%11,%12,%13,%14,%15,%16,%17,%18,%19,%20,%21,%22,%23,%24,%25,%26,%27,%28,%29,%30,%31,%32,%33,%34,%35,%36,%37,%38,%39,%40,%41,%42,%43,%44,%45,%46,%47,%48,%49,%50,%51,%52,%53,%54,%55,%56,%57,%58,%59,%60,%61,%62,%63}, {%64,%65,%66,%67}, %68, p, 1, 1, 0;\n}\n"
        : "+f"(d[0]), "+f"(d[1]), "+f"(d[2]), "+f"(d[3]), "+f"(d[4]), "+f"(d[5]), "+f"(d[6]), "+f"(d[7]), "+f"(d[8]), "+f"(d[9]), "+f"(d[10]), "+f"(d[11]), "+f"(d[12]), "+f"(d[13]), "+f"(d[14]), "+f"(d[15]), "+f"(d[16]), "+f"(d[17]), "+f"(d[18]), "+f"(d[19]), "+f"(d[20]), "+f"(d[21]), "+f"(d[22]), "+f"(d[23]), "+f"(d[24]), "+f"(d[25]), "+f"(d[26]), "+f"(d[27]), "+f"(d[28]), "+f"(d[29]), "+f"(d[30]), "+f"(d[31]), "+f"(d[32]), "+f"(d[33]), "+f"(d[34]), "+f"(d[35]), "+f"(d[36]), "+f"(d[37]), "+f"(d[38]), "+f"(d[39]), "+f"(d[40]), "+f"(d[41]), "+f"(d[42]), "+f"(d[43]), "+f"(d[44]), "+f"(d[45]), "+f"(d[46]), "+f"(d[47]), "+f"(d[48]), "+f"(d[49]), "+f"(d[50]), "+f"(d[51]), "+f"(d[52]), "+f"(d[53]), "+f"(d[54]), "+f"(d[55]), "+f"(d[56]), "+f"(d[57]), "+f"(d[58]), "+f"(d[59]), "+f"(d[60]), "+f"(d[61]), "+f"(d[62]), "+f"(d[63])
        : "r"(a[0]), "r"(a[1]), "r"(a[2]), "r"(a[3]), "l"(b), "r"(scale_d));
}
template <> __device__ __forceinline__ void wgmma_rs<192>(float (&d)[128], const uint32_t (&a)[4], uint64_t b, int scale_d) {
    asm volatile("{\n.reg .pred p;\nsetp.ne.b32 p, %101, 0;\nwgmma.mma_async.sync.aligned.m64n192k16.f32.bf16.bf16 {%0,%1,%2,%3,%4,%5,%6,%7,%8,%9,%10,%11,%12,%13,%14,%15,%16,%17,%18,%19,%20,%21,%22,%23,%24,%25,%26,%27,%28,%29,%30,%31,%32,%33,%34,%35,%36,%37,%38,%39,%40,%41,%42,%43,%44,%45,%46,%47,%48,%49,%50,%51,%52,%53,%54,%55,%56,%57,%58,%59,%60,%61,%62,%63,%64,%65,%66,%67,%68,%69,%70,%71,%72,%73,%74,%75,%76,%77,%78,%79,%80,%81,%82,%83,%84,%85,%86,%87,%88,%89,%90,%91,%92,%93,%94,%95}, {%96,%97,%98,%99}, %100, p, 1, 1, 0;\n}\n"
        : "+f"(d[0]), "+f"(d[1]), "+f"(d[2]), "+f"(d[3]), "+f"(d[4]), "+f"(d[5]), "+f"(d[6]), "+f"(d[7]), "+f"(d[8]), "+f"(d[9]), "+f"(d[10]), "+f"(d[11]), "+f"(d[12]), "+f"(d[13]), "+f"(d[14]), "+f"(d[15]), "+f"(d[16]), "+f"(d[17]), "+f"(d[18]), "+f"(d[19]), "+f"(d[20]), "+f"(d[21]), "+f"(d[22]), "+f"(d[23]), "+f"(d[24]), "+f"(d[25]), "+f"(d[26]), "+f"(d[27]), "+f"(d[28]), "+f"(d[29]), "+f"(d[30]), "+f"(d[31]), "+f"(d[32]), "+f"(d[33]), "+f"(d[34]), "+f"(d[35]), "+f"(d[36]), "+f"(d[37]), "+f"(d[38]), "+f"(d[39]), "+f"(d[40]), "+f"(d[41]), "+f"(d[42]), "+f"(d[43]), "+f"(d[44]), "+f"(d[45]), "+f"(d[46]), "+f"(d[47]), "+f"(d[48]), "+f"(d[49]), "+f"(d[50]), "+f"(d[51]), "+f"(d[52]), "+f"(d[53]), "+f"(d[54]), "+f"(d[55]), "+f"(d[56]), "+f"(d[57]), "+f"(d[58]), "+f"(d[59]), "+f"(d[60]), "+f"(d[61]), "+f"(d[62]), "+f"(d[63]), "+f"(d[64]), "+f"(d[65]), "+f"(d[66]), "+f"(d[67]), "+f"(d[68]), "+f"(d[69]), "+f"(d[70]), "+f"(d[71]), "+f"(d[72]), "+f"(d[73]), "+f"(d[74]), "+f"(d[75]), "+f"(d[76]), "+f"(d[77]), "+f"(d[78]), "+f"(d[79]), "+f"(d[80]), "+f"(d[81]), "+f"(d[82]), "+f"(d[83]), "+f"(d[84]), "+f"(d[85]), "+f"(d[86]), "+f"(d[87]), "+f"(d[88]), "+f"(d[89]), "+f"(d[90]), "+f"(d[91]), "+f"(d[92]), "+f"(d[93]), "+f"(d[94]), "+f"(d[95])
        : "r"(a[0]), "r"(a[1]), "r"(a[2]), "r"(a[3]), "l"(b), "r"(scale_d));
}
template <> __device__ __forceinline__ void wgmma_rs<256>(float (&d)[128], const uint32_t (&a)[4], uint64_t b, int scale_d) {
    asm volatile("{\n.reg .pred p;\nsetp.ne.b32 p, %133, 0;\nwgmma.mma_async.sync.aligned.m64n256k16.f32.bf16.bf16 {%0,%1,%2,%3,%4,%5,%6,%7,%8,%9,%10,%11,%12,%13,%14,%15,%16,%17,%18,%19,%20,%21,%22,%23,%24,%25,%26,%27,%28,%29,%30,%31,%32,%33,%34,%35,%36,%37,%38,%39,%40,%41,%42,%43,%44,%45,%46,%47,%48,%49,%50,%51,%52,%53,%54,%55,%56,%57,%58,%59,%60,%61,%62,%63,%64,%65,%66,%67,%68,%69,%70,%71,%72,%73,%74,%75,%76,%77,%78,%79,%80,%81,%82,%83,%84,%85,%86,%87,%88,%89,%90,%91,%92,%93,%94,%95,%96,%97,%98,%99,%100,%101,%102,%103,%104,%105,%106,%107,%108,%109,%110,%111,%112,%113,%114,%115,%116,%117,%118,%119,%120,%121,%122,%123,%124,%125,%126,%127}, {%128,%129,%130,%131}, %132, p, 1, 1, 0;\n}\n"
        : "+f"(d[0]), "+f"(d[1]), "+f"(d[2]), "+f"(d[3]), "+f"(d[4]), "+f"(d[5]), "+f"(d[6]), "+f"(d[7]), "+f"(d[8]), "+f"(d[9]), "+f"(d[10]), "+f"(d[11]), "+f"(d[12]), "+f"(d[13]), "+f"(d[14]), "+f"(d[15]), "+f"(d[16]), "+f"(d[17]), "+f"(d[18]), "+f"(d[19]), "+f"(d[20]), "+f"(d[21]), "+f"(d[22]), "+f"(d[23]), "+f"(d[24]), "+f"(d[25]), "+f"(d[26]), "+f"(d[27]), "+f"(d[28]), "+f"(d[29]), "+f"(d[30]), "+f"(d[31]), "+f"(d[32]), "+f"(d[33]), "+f"(d[34]), "+f"(d[35]), "+f"(d[36]), "+f"(d[37]), "+f"(d[38]), "+f"(d[39]), "+f"(d[40]), "+f"(d[41]), "+f"(d[42]), "+f"(d[43]), "+f"(d[44]), "+f"(d[45]), "+f"(d[46]), "+f"(d[47]), "+f"(d[48]), "+f"(d[49]), "+f"(d[50]), "+f"(d[51]), "+f"(d[52]), "+f"(d[53]), "+f"(d[54]), "+f"(d[55]), "+f"(d[56]), "+f"(d[57]), "+f"(d[58]), "+f"(d[59]), "+f"(d[60]), "+f"(d[61]), "+f"(d[62]), "+f"(d[63]), "+f"(d[64]), "+f"(d[65]), "+f"(d[66]), "+f"(d[67]), "+f"(d[68]), "+f"(d[69]), "+f"(d[70]), "+f"(d[71]), "+f"(d[72]), "+f"(d[73]), "+f"(d[74]), "+f"(d[75]), "+f"(d[76]), "+f"(d[77]), "+f"(d[78]), "+f"(d[79]), "+f"(d[80]), "+f"(d[81]), "+f"(d[82]), "+f"(d[83]), "+f"(d[84]), "+f"(d[85]), "+f"(d[86]), "+f"(d[87]), "+f"(d[88]), "+f"(d[89]), "+f"(d[90]), "+f"(d[91]), "+f"(d[92]), "+f"(d[93]), "+f"(d[94]), "+f"(d[95]), "+f"(d[96]), "+f"(d[97]), "+f"(d[98]), "+f"(d[99]), "+f"(d[100]), "+f"(d[101]), "+f"(d[102]), "+f"(d[103]), "+f"(d[104]), "+f"(d[105]), "+f"(d[106]), "+f"(d[107]), "+f"(d[108]), "+f"(d[109]), "+f"(d[110]), "+f"(d[111]), "+f"(d[112]), "+f"(d[113]), "+f"(d[114]), "+f"(d[115]), "+f"(d[116]), "+f"(d[117]), "+f"(d[118]), "+f"(d[119]), "+f"(d[120]), "+f"(d[121]), "+f"(d[122]), "+f"(d[123]), "+f"(d[124]), "+f"(d[125]), "+f"(d[126]), "+f"(d[127])
        : "r"(a[0]), "r"(a[1]), "r"(a[2]), "r"(a[3]), "l"(b), "r"(scale_d));
}

template <int I> __device__ __forceinline__ void conv_load_a(uint32_t (&a)[16][4], const uint32_t (&hx)[8]) {
    constexpr int IP = I >> 2, SG = I & 3;
    a[I][0] = lds32_o<-1024 * IP>(hx[2 * SG]); a[I][1] = lds32_o<-1024 * IP - 512>(hx[2 * SG]);
    a[I][2] = lds32_o<-1024 * IP>(hx[2 * SG + 1]); a[I][3] = lds32_o<-1024 * IP - 512>(hx[2 * SG + 1]);
    if constexpr (I < 15) conv_load_a<I + 1>(a, hx);
}
template <int I> __device__ __forceinline__ void conv_issue(float (&acc)[128], const uint32_t (&a)[16][4], uint64_t db) {
    wgmma_rs<256 - 64 * (I >> 2)>(acc, a[I], db + 64 * (I >> 2) + 2 * (I & 3), I != 0);
    if constexpr (I < 15) conv_issue<I + 1>(acc, a, db);
}
__device__ __forceinline__ void conv_frag_addr(uint32_t (&hx)[8], uint32_t copy_base, int w0, uint32_t xb) {
#pragma unroll
    for (int i = 0; i < 8; i++) { const uint32_t W = (uint32_t)(w0 - 4 * i); hx[i] = copy_base + ((W ^ (((W >> 5) & 3u) << 2) ^ xb) << 2); }
}

__device__ __forceinline__ void kv_cta(const Params& p, uint32_t sb, int j) {
    constexpr uint32_t IN_BYTES = 17408 + 16384, OFF_V = 17408;
    constexpr uint32_t OFF_OUT = 4 * IN_BYTES, OFF_TAPS = OFF_OUT + 4 * 16384;
    constexpr uint32_t B_INF = 0, B_INE = 32, B_OUTF = 64, B_OUTE = 96;
    const uint32_t bars = sb + OFF_BAR;
    const int tid = threadIdx.x, lane = tid & 31;
    if (tid == 0) {
        for (int s = 0; s < 4; s++) { mbar_init(bars + B_INF + 8 * s, 1); mbar_init(bars + B_INE + 8 * s, 8); mbar_init(bars + B_OUTF + 8 * s, 8); mbar_init(bars + B_OUTE + 8 * s, 1); }
        asm volatile("fence.mbarrier_init.release.cluster;" ::: "memory");
    }
    for (int i = tid; i < 512; i += 384) { const uint4 t = __ldg(reinterpret_cast<const uint4*>(p.shift_k) + i); sts128(sb + OFF_TAPS + i * 16, t.x, t.y, t.z, t.w); }
    __syncthreads();
    if (tid == 0) {
        const uint64_t pol = policy_evict_first();
#pragma unroll 1
        for (int i = 0; i < 64 + 3; i++) {
            if (i < 64) {
                const int bf = i & 3, t0 = j * 512 + (i >> 3) * 64, c0 = (i & 7) * 128;
                if (i >= 4) mbar_wait(bars + B_INE + 8 * bf, ((i >> 2) - 1) & 1);
                mbar_expect_tx(bars + B_INF + 8 * bf, 67 * 256 + 64 * 256);
                tma_2d_h(sb + bf * IN_BYTES, &p.tmK, c0, t0 - 3, bars + B_INF + 8 * bf, pol);
                tma_2d_h(sb + bf * IN_BYTES + OFF_V, &p.tmV, c0, t0, bars + B_INF + 8 * bf, pol);
            }
            if (i >= 3) {
                const int o = i - 3, bf = o & 3;
                mbar_wait(bars + B_OUTF + 8 * bf, (o >> 2) & 1);
                if ((o & 7) == 0) H3_GSTAMP(o >> 3);
                tma_store_2d(&p.tmKvT, sb + OFF_OUT + bf * 16384, 1984 - (j * 512 + (o >> 3) * 64), (o & 7) * 128);
                bulk_commit();
                asm volatile("cp.async.bulk.wait_group.read 1;" ::: "memory");
                if (o > 0) mbar_arrive(bars + B_OUTE + 8 * ((o - 1) & 3));
            }
        }
        bulk_wait_all();
        flag_add_after_bulk(p.flags + FL_KV * FLAG_STRIDE);
        H3_GSTAMP(31);
    } else if (tid >= 32) {
#pragma unroll 1
        for (int u = (tid >> 5) - 1; u < 512; u += 11) {
            const int i = u >> 3, bf = i & 3, o = u & 7;
            mbar_wait(bars + B_INF + 8 * bf, (i >> 2) & 1);
            if (i >= 4) mbar_wait(bars + B_OUTE + 8 * bf, ((i >> 2) - 1) & 1);
            const uint32_t out = sb + OFF_OUT + bf * 16384;
            const uint32_t odd = (lane >> 2) & 1, sel0 = odd ? 0x7632u : 0x5410u, sel1 = odd ? 0x5410u : 0x7632u;
            uint32_t kk[2][11], vv[2][8];
            uint4 sw[2];
#pragma unroll
            for (int it = 0; it < 2; it++) {
                const uint32_t rd = sb + bf * IN_BYTES + o * 8 * 256 + (it * 32 + lane) * 4;
#pragma unroll
                for (int r = 0; r < 11; r++) kk[it][r] = lds32(rd + r * 256);
#pragma unroll
                for (int r = 0; r < 8; r++) vv[it][r] = lds32(rd + OFF_V + r * 256);
                sw[it] = lds128(sb + OFF_TAPS + ((i & 7) * 64 + it * 32 + lane) * 16);
            }
#pragma unroll
            for (int it = 0; it < 2; it++) {
                const uint32_t w0 = __byte_perm(sw[it].x, sw[it].z, 0x5410), w1 = __byte_perm(sw[it].x, sw[it].z, 0x7632);
                const uint32_t w2 = __byte_perm(sw[it].y, sw[it].w, 0x5410), w3 = __byte_perm(sw[it].y, sw[it].w, 0x7632);
#pragma unroll
                for (int r = 0; r < 8; r++)
                    vv[it][r] = bf2_mul(bf2_add(bf2_add(bf2_add(bf2_mul(kk[it][r], w3), bf2_mul(kk[it][r + 1], w2)), bf2_mul(kk[it][r + 2], w1)), bf2_mul(kk[it][r + 3], w0)), vv[it][r]);
                const uint32_t r0 = 2 * (it * 32 + lane) + odd, r1 = r0 ^ 1;
                const uint32_t* v = vv[it];
                sts128(out + r0 * 128 + (((7 - o) ^ (r0 & 7)) << 4), __byte_perm(v[0], v[1], sel0), __byte_perm(v[2], v[3], sel0), __byte_perm(v[4], v[5], sel0), __byte_perm(v[6], v[7], sel0));
                sts128(out + r1 * 128 + (((7 - o) ^ (r1 & 7)) << 4), __byte_perm(v[0], v[1], sel1), __byte_perm(v[2], v[3], sel1), __byte_perm(v[4], v[5], sel1), __byte_perm(v[6], v[7], sel1));
            }
            fence_async_smem();
            __syncwarp();
            if (lane == 0) { mbar_arrive(bars + B_INE + 8 * bf); mbar_arrive(bars + B_OUTF + 8 * bf); }
        }
    }
}

__global__ void __launch_bounds__(384, 1) h3_kernel(const __grid_constant__ Params p) {
    extern __shared__ uint8_t smem_raw[];
    const uint32_t sb = (smem_u32(smem_raw) + 1023) & ~1023u;
    const uint32_t bars = sb + OFF_BAR;
    const int tid = threadIdx.x;
    const int wg = __shfl_sync(0xffffffffu, tid >> 7, 0);
    const int lane = tid & 31;
    const int cta = blockIdx.x;
    const int pair = cta >> 1;
    const uint32_t rank = cta & 1;

    if (cta >= NCTA) { kv_cta(p, sb, cta - NCTA); return; }

    uint32_t x[32];
    if (wg != 0) {
        const uint4* src = reinterpret_cast<const uint4*>(p.q + (size_t)(cta * 16 + ((tid >> 5) - 4) * 2 + (lane >> 4)) * D) + (lane & 15);
#pragma unroll
        for (int i = 0; i < 8; i++) { const uint4 t = __ldg(src + i * 16); x[4 * i] = t.x; x[4 * i + 1] = t.y; x[4 * i + 2] = t.z; x[4 * i + 3] = t.w; }
    }
    if (tid == 0) {
        H3_STAMP(0);
#pragma unroll 1
        for (int s = 0; s < 4; s++) { mbar_init(bars + BAR_FULLA + 8 * s, 1); mbar_init(bars + BAR_EMPTYA + 8 * s, 4); }
#pragma unroll 1
        for (int s = 0; s < 6; s++) { mbar_init(bars + BAR_FULLB + 8 * s, 1); mbar_init(bars + BAR_EMPTYB + 8 * s, 4); }
        mbar_init(bars + BAR_STGFULL, 8);
        mbar_init(bars + BAR_STGEMPTY, 1);
        mbar_init(bars + BAR_ALTFULL, 8);
        mbar_init(bars + BAR_ALT2FULL, 8);
        mbar_init(bars + BAR_OPFULL, 1);
        asm volatile("fence.mbarrier_init.release.cluster;" ::: "memory");
    }
    __syncthreads();
    cluster_arrive();

    const int m1 = cta & 15;
    const int nb1 = cta >> 4;
    const int m2 = pair >> 2;
    const int nh = 24 + (pair & 3);
    const int n2 = (pair & 3) * 256 + (int)rank * 128;

    if (wg == 0) {
        asm volatile("setmaxnreg.dec.sync.aligned.u32 40;\n");
        const int warp = tid >> 5;
        if (warp == 0) {
            if (lane == 0) {
                const uint64_t pol = policy_evict_first();
                const int mrow1 = m1 * 128, mrow2 = m2 * 128 + (int)rank * 64, ngh = nh * 2 + (int)rank;
                const CUtensorMap* tmW = rank ? &p.tmWu2 : &p.tmWg2;
                const uint32_t woff = 16384 + rank * 16384;
                cluster_wait();
#pragma unroll 1
                for (int j = 0; j < 4; j++) {
                    const uint32_t full = bars + BAR_FULLA + 8 * j;
                    mbar_expect_tx(full, A_STAGE);
                    tma_3d_mc_h(sb + j * A_STAGE + woff, tmW, 0, j * 64, nb1 * 2, full, pol);
                }
                flag_wait(p.flags + (FL_XN + m1) * FLAG_STRIDE, 64);
                H3_STAMP(1);
#pragma unroll 1
                for (int j = 0; j < 4; j++) tma_2d(sb + j * A_STAGE, &p.tmXn128, j * 64, mrow1, bars + BAR_FULLA + 8 * j);
#pragma unroll 1
                for (int g = 4; g < 48; g++) {
                    const int st = g & 3, k0 = (g & 15) * 64, ng = ((g >> 4) * 8 + nb1) * 2;
                    const uint32_t full = bars + BAR_FULLA + 8 * st, a = sb + st * A_STAGE;
                    mbar_wait(bars + BAR_EMPTYA + 8 * st, ((g >> 2) - 1) & 1);
                    H3_TR(1, 256 + g);
                    mbar_expect_tx(full, A_STAGE);
                    tma_2d(a, &p.tmXn128, k0, mrow1, full);
                    tma_3d_mc_h(a + woff, tmW, 0, k0, ng, full, pol);
                    if (g == 3 * ((cta & 31) >> 2) - 2) { pf_bulk_h(p.k + (size_t)cta * 16 * D, 32768, pol); pf_bulk_h(p.v + (size_t)cta * 16 * D, 32768, pol); }
                }
                flag_wait(p.flags + (FL_XN + m2) * FLAG_STRIDE, 64);
                pf_bulk_h(p.ssm_k + (size_t)cta * 8 * S, 32768, pol);
                int st = 0; uint32_t ph = 1;
#pragma unroll 1
                for (int e = 0; e < 16; e++) {
                    const uint32_t full = bars + BAR_FULLB + 8 * st, a = sb + st * B_STAGE;
                    if (e < 6) {
                        if (e != 2 && e != 5) mbar_wait(bars + BAR_EMPTYA + 8 * (e - (e >= 3)), 1);
                    } else {
                        mbar_wait(bars + BAR_EMPTYB + 8 * st, ph);
                    }
                    H3_TR(1, 304 + e);
                    mbar_expect_tx(full, B_STAGE);
                                        tma_2d_mc(a + rank * 8192, &p.tmXn64, e * 64, mrow2, full);
                    tma_3d_h(a + 16384, &p.tmWg1, 0, e * 64, ngh, full, pol);
                    tma_3d_h(a + 24576, &p.tmWu1, 0, e * 64, ngh, full, pol);
                    if (++st == 6) { st = 0; ph ^= 1; }
                }
                mbar_wait(bars + BAR_EMPTYB + 8 * ST_H, 1);
                mbar_expect_tx(bars + BAR_FULLB + 8 * ST_H, 32768);
                bulk_g2s_h(sb + ST_H * B_STAGE, p.ssm_k + (size_t)cta * 8 * S, 32768, bars + BAR_FULLB + 8 * ST_H, pol);
                unsigned kv_ready;
                asm volatile("ld.acquire.gpu.global.u32 %0, [%1];" : "=r"(kv_ready) : "l"(p.flags + FL_KV * FLAG_STRIDE) : "memory");
#pragma unroll 1
                for (int pass = 0; pass < 2; pass++) {
                    if ((pass == 0) == (kv_ready >= 4)) {
                        mbar_wait(bars + BAR_EMPTYB + 8 * ST_U, 1);
                        flag_wait(p.flags + FL_KV * FLAG_STRIDE, 4);
                        mbar_expect_tx(bars + BAR_FULLB + 8 * ST_U, 32768);
#pragma unroll 1
                        for (int ch = 0; ch < 8; ch++) bulk_g2s_h(sb + ST_U * B_STAGE + ch * U_PITCH, p.kvT + (size_t)(cta * 8 + ch) * S, 4096, bars + BAR_FULLB + 8 * ST_U, pol);
                    }
                    if (pass == 0) {
#pragma unroll 1
                        for (int c = 0; c < 4; c++) { mbar_wait(bars + BAR_EMPTYB + 8 * c, 0); mbar_arrive(bars + BAR_FULLB + 8 * c); }
                    }
                }
                flag_wait(p.flags + (FL_H + m2) * FLAG_STRIDE, 16);
                H3_STAMP(2);
                int i6 = 0; uint32_t rho = 0;
#pragma unroll 1
                for (int kb = 0; kb < 56; kb++) {
                    const int sg = (0x512034 >> (4 * i6)) & 15;
                    const uint32_t par = ((0x21u >> i6) & 1u) ^ rho;
                    const uint32_t full = bars + BAR_FULLB + 8 * sg, a = sb + sg * B_STAGE;
                    mbar_wait(bars + BAR_EMPTYB + 8 * sg, par ^ 1);
                    if (kb == 32) flag_wait(p.flags + (FL_H2 + m2) * FLAG_STRIDE, 16);
                    H3_TR(2, 256 + kb);
                    mbar_expect_tx(full, B_STAGE);
                    tma_2d_mc(a + rank * 8192, &p.tmH64, kb * 64, mrow2, full);
                    tma_3d(a + 16384, &p.tmWd, 0, kb * 64, n2 >> 6, full);
                    if (++i6 == 6) { i6 = 0; rho ^= 1; }
                }
                mbar_wait(bars + BAR_EMPTYB + 0, 0);
                mbar_expect_tx(bars + BAR_FULLB + 0, 32768);
                tma_2d(sb, &p.tmX128, n2, m2 * 128, bars + BAR_FULLB + 0);
                tma_2d(sb + 16384, &p.tmX128, n2 + 64, m2 * 128, bars + BAR_FULLB + 0);
                mbar_wait(bars + BAR_OPFULL, 0);
                unsigned old;
                asm volatile("atom.acq_rel.gpu.global.add.u32 %0, [%1], 1;" : "=r"(old) : "l"(p.flags + FL_DONE * FLAG_STRIDE) : "memory");
                if (old == NCTA - 1) {
#pragma unroll 1
                    for (int i = 0; i < FL_COUNT; i++) p.flags[i * FLAG_STRIDE] = 0;
                }
            } else {
                cluster_wait();
            }
        } else {
            if (tid == 32) H3_GSTAMP(30);
            cluster_wait();
            const int wt = tid - 32;
#pragma unroll 1
            for (int Ri = 0; Ri < 7; Ri++) {
                const int R = (Ri == 5) ? 6 : (Ri == 6) ? 5 : Ri;
                const uint32_t buf = (R == 4) ? sb + ST_ALT2 * B_STAGE : (R == 6) ? sb + ST_ALT * B_STAGE : sb + OFF_STG;
                mbar_wait_idle(bars + ((R == 4) ? BAR_ALT2FULL : (R == 6) ? BAR_ALTFULL : BAR_STGFULL), (R < 4) ? (R & 1) : 0);
                if (wt == 0) H3_TR(3, 200 + R * 4);
#pragma unroll 1
                for (int i0 = wt; i0 < 1024; i0 += 2 * 96) {
                    const int i1 = i0 + 96;
                    const uint32_t a0 = buf + (i0 >> 9) * 16384 + (i0 & 511) * 16;
                    const uint32_t a1 = (i1 < 1024) ? buf + (i1 >> 9) * 16384 + (i1 & 511) * 16 : a0;
                    uint4 g0 = lds128(a0), u0 = lds128(a0 + 8192), g1 = lds128(a1), u1 = lds128(a1 + 8192);
                    g0.x = bf2_mul(silu_bf2(g0.x), u0.x); g0.y = bf2_mul(silu_bf2(g0.y), u0.y); g0.z = bf2_mul(silu_bf2(g0.z), u0.z); g0.w = bf2_mul(silu_bf2(g0.w), u0.w);
                    g1.x = bf2_mul(silu_bf2(g1.x), u1.x); g1.y = bf2_mul(silu_bf2(g1.y), u1.y); g1.z = bf2_mul(silu_bf2(g1.z), u1.z); g1.w = bf2_mul(silu_bf2(g1.w), u1.w);
                    sts128(a0, g0.x, g0.y, g0.z, g0.w);
                    if (i1 < 1024) sts128(a1, g1.x, g1.y, g1.z, g1.w);
                }
                if (wt == 0) H3_TR(3, 200 + R * 4 + 1);
                fence_async_smem();
                bar_sync(4, 96);
                if (wt == 0) {
                    const int mm = (R < 6) ? m1 : m2;
                    const int col = (R < 6) ? (8 * (R >> 1) + nb1) * 128 + (R & 1) * 64 : nh * 128 + (int)rank * 64;
                    tma_store_2d(&p.tmH64, buf, col, mm * 128);
                    tma_store_2d(&p.tmH64, buf + 16384, col, mm * 128 + 64);
                    bulk_commit();
                    bulk_wait_read();
                    if (R != 4 && R != 6) mbar_arrive(bars + BAR_STGEMPTY);
                    else {
                        const uint32_t eb = bars + BAR_EMPTYB + 8 * ((R == 4) ? ST_ALT2 : ST_ALT);
                        mbar_arrive_cta(eb, 0); mbar_arrive_cta(eb, 0); mbar_arrive_cta(eb, 1); mbar_arrive_cta(eb, 1);
                    }
                    H3_TR(3, 200 + R * 4 + 2);
                    if (R == 1 || R == 3 || R >= 5) {
                        bulk_wait_all();
                        flag_add_after_bulk(p.flags + ((R < 4 ? FL_H : FL_H2) + mm) * FLAG_STRIDE);
                    }
                }
            }
            if (wt == 0) {
                mbar_wait(bars + BAR_FULLB + 8 * 3, 0); mbar_wait(bars + BAR_FULLB + 8 * 3, 1); mbar_wait(bars + BAR_FULLB + 8 * 3, 0);
                pf_2d(&p.tmX128, n2, m2 * 128); pf_2d(&p.tmX128, n2 + 64, m2 * 128);
                flag_wait(p.flags + (FL_Y + (n2 >> 7)) * FLAG_STRIDE, 128);
                mbar_expect_tx(bars + BAR_OPFULL, 32768);
                tma_2d(sb + OFF_STG, &p.tmY2T, 1984 - m2 * 128, n2, bars + BAR_OPFULL);
                tma_2d(sb + OFF_STG + 16384, &p.tmY2T, 1920 - m2 * 128, n2, bars + BAR_OPFULL);
            }
        }
        __syncwarp();
        cluster_sync();
    } else {
        asm volatile("setmaxnreg.inc.sync.aligned.u32 232;\n");
        const int cw = wg - 1;
        const int w = (tid >> 5) & 3;
        const int wtid = tid & 127;

        {
            const int rl = (cw * 4 + w) * 2 + (lane >> 4);
            const uint32_t src = sb + OFF_STG + rl * 2048 + (lane & 15) * 16;
            if (tid == 128) H3_STAMP(15);
            float s0 = 0.f, s1 = 0.f, s2 = 0.f, s3 = 0.f;
#pragma unroll
            for (int i = 0; i < 32; i += 2) { s0 += bf_lo(x[i]); s1 += bf_hi(x[i]); s2 += bf_lo(x[i + 1]); s3 += bf_hi(x[i + 1]); }
            float s = (s0 + s1) + (s2 + s3);
#pragma unroll
            for (int o = 8; o > 0; o >>= 1) s += __shfl_xor_sync(0xffffffffu, s, o);
            const float mu = s * (1.0f / D);
            s0 = s1 = s2 = s3 = 0.f;
#pragma unroll
            for (int i = 0; i < 32; i += 2) {
                const float a = bf_lo(x[i]) - mu, b = bf_hi(x[i]) - mu, c = bf_lo(x[i + 1]) - mu, d = bf_hi(x[i + 1]) - mu;
                s0 = fmaf(a, a, s0); s1 = fmaf(b, b, s1); s2 = fmaf(c, c, s2); s3 = fmaf(d, d, s3);
            }
            float v = (s0 + s1) + (s2 + s3);
#pragma unroll
            for (int o = 8; o > 0; o >>= 1) v += __shfl_xor_sync(0xffffffffu, v, o);
            if (tid == 128) H3_STAMP(17);
            const uint32_t mu2 = pack_bf2(mu, mu);
            const float vb = bf_lo(pack_bf2(v * (1.0f / D), 0.f));
            const float ve = bf_lo(pack_bf2(vb + 1e-5f, 0.f));
            const float sd = bf_lo(pack_bf2(sqrtf(ve), 0.f));
            const float inv = __frcp_rn(sd);
#pragma unroll
            for (int i = 0; i < 8; i++) {
                uint32_t oo[4];
#pragma unroll
                for (int e = 0; e < 4; e++) { const uint32_t dd = bf2_sub(x[4 * i + e], mu2); oo[e] = pack_bf2(bf_lo(dd) * inv, bf_hi(dd) * inv); }
                sts128(src + i * 256, oo[0], oo[1], oo[2], oo[3]);
            }
            if ((lane & 15) == 0) asm volatile("st.shared.v2.b32 [%0], {%1, %2};" :: "r"(bars + OFF_STAT + rl * 8), "r"(mu2), "r"(__float_as_uint(inv)) : "memory");
            fence_async_smem();
            __syncwarp();
            if (tid == 128) H3_STAMP(18);
            if (lane == 0) {
                bulk_s2g(p.xn + (size_t)(cta * 16 + (cw * 4 + w) * 2) * D, sb + OFF_STG + (cw * 4 + w) * 4096, 4096);
                bulk_s2g(p.stats + cta * 16 + (cw * 4 + w) * 2, bars + OFF_STAT + (cw * 4 + w) * 16, 16);
                bulk_commit();
                bulk_wait_all();
                flag_add_after_bulk(p.flags + (FL_XN + (cta >> 3)) * FLAG_STRIDE);
            }
            if (tid == 128) H3_STAMP(19);
            bar_sync(3, 256);
        }
        if (tid == 128) H3_STAMP(3);
        cluster_wait();

        const uint32_t lrow = w * 16 + (lane & 7) + ((lane >> 3) & 1) * 8;
        const uint32_t lrow7 = lane & 7;
        const uint32_t lgrp = lane >> 4;
        const uint32_t stg_lane = sb + OFF_STG + cw * 16384 + lrow * 128;
        const uint64_t descA = make_desc(sb + cw * 8192, 16, 1024);
        const uint64_t descB = make_desc(sb + 16384, 8192, 1024);

        int st = 0; uint32_t ph = 0;
        uint32_t pg[32], pu[32], qg[16], qu[16];
        {
            float acc[128];
            int prev = 0;
#pragma unroll 1
            for (int g = 0; g < 64; g++) {
                const int kb = g & 15;
                if (g < 48) {
                    const int sa = g & 3;
                    mbar_wait(bars + BAR_FULLA + 8 * sa, (g >> 2) & 1);
                    if (g == 0 && tid == 128) H3_STAMP(4);
                    if (wtid == 0) H3_TR(1, cw * 128 + g * 2);
                    const uint64_t da = descA + sa * (A_STAGE >> 4), db = descB + sa * (A_STAGE >> 4);
                    wg_fence();
                    wgmma_256(acc, da, db, kb != 0);
#pragma unroll
                    for (int k = 1; k < 4; k++) wgmma_256(acc, da + k * 2, db + k * 128, 1);
                    wg_commit();
                } else {
                    mbar_wait(bars + BAR_FULLB + 8 * st, ph);
                    if (wtid == 0) H3_TR(1, cw * 128 + g * 2);
                    const uint64_t da = descA + st * (B_STAGE >> 4), db = descB + st * (B_STAGE >> 4);
                    wg_fence();
                    wgmma_128_lo(acc, da, db, kb != 0);
#pragma unroll
                    for (int k = 1; k < 4; k++) wgmma_128_lo(acc, da + k * 2, db + k * 128, 1);
                    wg_commit();
                }
                wg_wait<1>();
                if (wtid == 0) H3_TR(1, cw * 128 + g * 2 + 1);
                if (kb > 0) {
                    if (wtid < 2) mbar_arrive_cta(bars + ((g > 48) ? BAR_EMPTYB + 8 * prev : BAR_EMPTYA + 8 * ((g - 1) & 3)), wtid);
                }
                if (g >= 48) { prev = st; if (++st == 6) { st = 0; ph ^= 1; } }
                if (g >= 16 && g < 48) {
                    const int pc = (kb < 4) ? kb : ((kb >= 9 && kb < 13) ? kb - 5 : -1);
                    if (pc >= 0) {
                        if (pc == 0 && g >= 32) mbar_wait(bars + BAR_STGEMPTY, 1);
                        if (pc == 4) mbar_wait(bars + BAR_STGEMPTY, 0);
                        stage_piece_dyn(pc, pg, pu, stg_lane, lrow7, lgrp);
                        if ((pc & 3) == 3) { __syncwarp(); if (lane == 0) mbar_arrive(bars + BAR_STGFULL); }
                    }
                }
                if (kb == 15 && g < 48) {
                    wg_wait<0>();
                    if (wtid == 0) H3_TR(1, 330 + cw * 16 + (g >> 4) * 2);
                    if (wtid < 2) mbar_arrive_cta(bars + BAR_EMPTYA + 24, wtid);
#pragma unroll
                    for (int i = 0; i < 32; i++) { pg[i] = pack_bf2(acc[2 * i], acc[2 * i + 1]); pu[i] = pack_bf2(acc[64 + 2 * i], acc[64 + 2 * i + 1]); }
                    if (wtid == 0) H3_TR(1, 330 + cw * 16 + (g >> 4) * 2 + 1);
                    if (tid == 128) H3_STAMP(5 + (g >> 4));
                }
            }
            wg_wait<0>();
            if (wtid < 2) mbar_arrive_cta(bars + BAR_EMPTYB + 8 * prev, wtid);
#pragma unroll
            for (int i = 0; i < 16; i++) { qg[i] = pack_bf2(acc[2 * i], acc[2 * i + 1]); qu[i] = pack_bf2(acc[32 + 2 * i], acc[32 + 2 * i + 1]); }
            if (tid == 128) H3_STAMP(14);
        }
        mbar_wait(bars + BAR_FULLB + 8 * ST_ALT2, 1);
        {
            const uint32_t alt_lane = sb + ST_ALT2 * B_STAGE + cw * 16384 + lrow * 128;
            stage_piece<0>(pg, pu, alt_lane, lrow7, lgrp); stage_piece<1>(pg, pu, alt_lane, lrow7, lgrp);
            stage_piece<2>(pg, pu, alt_lane, lrow7, lgrp); stage_piece<3>(pg, pu, alt_lane, lrow7, lgrp);
            __syncwarp(); if (lane == 0) mbar_arrive(bars + BAR_ALT2FULL);
        }
        mbar_wait(bars + BAR_STGEMPTY, 1);
        stage_piece<4>(pg, pu, stg_lane, lrow7, lgrp); stage_piece<5>(pg, pu, stg_lane, lrow7, lgrp);
        stage_piece<6>(pg, pu, stg_lane, lrow7, lgrp); stage_piece<7>(pg, pu, stg_lane, lrow7, lgrp);
        __syncwarp(); if (lane == 0) mbar_arrive(bars + BAR_STGFULL);
        mbar_wait(bars + BAR_FULLB + 8 * ST_ALT, 1);
        {
            const uint32_t alt_lane = sb + ST_ALT * B_STAGE + cw * 16384 + lrow * 128;
#pragma unroll
            for (int i = 0; i < 4; i++) {
                const uint32_t addr = alt_lane + (((2 * i + lgrp) ^ lrow7) << 4);
                stsm_x4(addr, qg[4 * i], qg[4 * i + 1], qg[4 * i + 2], qg[4 * i + 3]);
                stsm_x4(addr + 8192, qu[4 * i], qu[4 * i + 1], qu[4 * i + 2], qu[4 * i + 3]);
            }
            __syncwarp(); if (lane == 0) mbar_arrive(bars + BAR_ALTFULL);
        }
        if (tid == 128) H3_STAMP(8);
        {
            const int r = lane >> 2, c4 = lane & 3;
            if (lane == 0) H3_TR(3, (cw * 4 + w) * 16 + 0);
            mbar_wait(bars + BAR_FULLB + 8 * ST_H, 0);
            mbar_wait(bars + BAR_FULLB + 8 * ST_C0, 1);
            mbar_wait(bars + BAR_FULLB + 8 * ST_C1, 1);
            if (tid == 128) H3_STAMP(23);
            {
                const uint32_t sH = sb + ST_H * B_STAGE + (cw * 4 + w) * 4096;
                const uint32_t sA = sb + (w >> 1) * B_STAGE + ((w & 1) * 2 + cw) * 8192, sB = sA + 4096;
                uint4 hv[8]; uint32_t hp[8];
#pragma unroll
                for (int i = 0; i < 8; i++) {
                    const int Q = i * 32 + lane;
                    hv[i] = lds128(sH + (255 - Q) * 16);
                    hp[i] = lds32(sH + (254 - Q) * 16 + 12);
                }
                if (lane == 31) hp[7] = 0;
                const uint32_t qs = (uint32_t)(lane ^ ((lane >> 3) & 3)) * 16;
#pragma unroll
                for (int i = 0; i < 8; i++) {
                    const uint4 a = hv[i];
                    const uint32_t prev = hp[i];
                    sts128(sA + i * 512 + qs, __byte_perm(a.w, 0, 0x1032), __byte_perm(a.z, 0, 0x1032), __byte_perm(a.y, 0, 0x1032), __byte_perm(a.x, 0, 0x1032));
                    sts128(sB + i * 512 + (qs ^ 64), __byte_perm(a.w, a.z, 0x7610), __byte_perm(a.z, a.y, 0x7610), __byte_perm(a.y, a.x, 0x7610), __byte_perm(a.x, prev, 0x7610));
                }
            }
            if (tid == 128) H3_STAMP(24);
            mbar_wait(bars + BAR_FULLB + 8 * ST_U, 0);
            if (tid == 128) H3_STAMP(25);
            if (lane < 8) sts128(sb + ST_U * B_STAGE + (cw * 4 + w) * U_PITCH + 4096 + lane * 16, 0, 0, 0, 0);
            fence_async_smem();
            bar_sync(1 + cw, 128);
            if (wtid < 2) mbar_arrive_cta(bars + BAR_EMPTYB + 8 * ST_H, wtid);
            if (cw == 1) bar_arrive(5, 256);
            if (tid == 128) H3_STAMP(9);
            const uint32_t podd = r & 1, b0 = (r >> 1) & 1, b1 = r >> 2;
            const int w0 = 1023 - w + c4 - 32 * (r >> 1);
            const uint32_t cpy = podd ? 0u : 4096u, xb = podd ? 0u : 16u;
            const int y0 = 2 * w + (int)podd - 2 * c4;
            const uint32_t mask0 = (r >> 1) ? 0xFFFFFFFFu : ((y0 >= 0 ? 0x0000FFFFu : 0u) | (y0 >= 1 ? 0xFFFF0000u : 0u));
            uint32_t a[16][4];
            {
                uint32_t hx[8];
                conv_frag_addr(hx, sb + cw * 8192 + cpy, w0, xb);
                conv_load_a<0>(a, hx);
                a[0][0] &= mask0;
            }
            const uint2 dq = __ldg(reinterpret_cast<const uint2*>(p.ssm_D + cta * 8 + cw * 4));
            auto conv_finish = [&](int cp) {
                const uint32_t sA = sb + (cp >> 1) * B_STAGE + ((cp & 1) * 2 + cw) * 8192;
                const uint32_t sU = sb + ST_U * B_STAGE + (cw * 4 + cp) * U_PITCH;
                const uint32_t dw = (cp & 2) ? dq.y : dq.x;
                const uint32_t d2 = __byte_perm(dw, 0, (cp & 1) ? 0x3232 : 0x1010);
#pragma unroll
                for (int i = 0; i < 2; i++) {
                    const uint32_t beta = 64 * w + 32 * i + lane;
                    const uint4 kv = lds128(sU + beta * 16);
                    const uint32_t y0w = lds32_o<0>(sA + beta * 4), y1w = lds32_o<1024>(sA + beta * 4), y2w = lds32_o<2048>(sA + beta * 4), y3w = lds32_o<3072>(sA + beta * 4);
                    sts128(sU + beta * 16, bf2_add(y0w, bf2_mul(kv.x, d2)), bf2_add(y1w, bf2_mul(kv.y, d2)), bf2_add(y2w, bf2_mul(kv.z, d2)), bf2_add(y3w, bf2_mul(kv.w, d2)));
                }
            };
            auto conv_store = [&](int cp) {
                const int ch = cw * 4 + cp;
                fence_async_smem();
                __syncwarp();
                if (lane == 0) { bulk_s2g(p.y2T + (size_t)(cta * 8 + ch) * S + w * 512, sb + ST_U * B_STAGE + ch * U_PITCH + w * 1024, 1024); bulk_commit(); }
                if (cp & 1) { bar_sync(1 + cw, 128); if (wtid < 2) mbar_arrive_cta(bars + BAR_EMPTYB + 8 * (cp >> 1), wtid); }
                if (lane == 0) H3_TR(3, (cw * 4 + w) * 16 + 3 + cp * 3);
            };
#pragma unroll 1
            for (int ci = 0; ci < 4; ci++) {
                const int k = 2 * ci + cw;
                float acc[128];
                if (lane == 0) H3_TR(3, (cw * 4 + w) * 16 + 1 + ci * 3);
                bar_sync(5 + cw, 256);
                wg_fence();
                conv_issue<0>(acc, a, make_desc_noswz(sb + ST_U * B_STAGE + (cw * 4 + ci) * U_PITCH, 16, 128));
                wg_commit();
                if (k < 7) bar_arrive(5 + (cw ^ 1), 256);
                if (ci > 0) conv_finish(ci - 1);
                wg_wait<0>();
                if (lane == 0) H3_TR(3, (cw * 4 + w) * 16 + 2 + ci * 3);
                if (ci > 0) conv_store(ci - 1);
                float f[16];
                {
                    float wv[34];
#pragma unroll
                    for (int i = 0; i < 16; i++) {
#pragma unroll
                        for (int jj = 0; jj < 2; jj++) {
                            const float ve = acc[8 * i + jj] + ((2 * i + 4 < 32) ? acc[4 * (2 * i + 4) + 2 + jj] : 0.f);
                            const float vo = acc[8 * i + 4 + jj] + ((2 * i + 5 < 32) ? acc[4 * (2 * i + 5) + 2 + jj] : 0.f);
                            const float vn = (i < 15) ? acc[8 * i + 8 + jj] + ((2 * i + 6 < 32) ? acc[4 * (2 * i + 6) + 2 + jj] : 0.f) : 0.f;
                            wv[2 * i + jj] = (b0 ? vn : ve) + __shfl_xor_sync(0xffffffffu, vo, 8);
                        }
                    }
                    wv[32] = wv[33] = 0.f;
#pragma unroll
                    for (int kk = 0; kk < 8; kk++)
#pragma unroll
                        for (int jj = 0; jj < 2; jj++)
                            f[2 * kk + jj] = (b1 ? wv[4 * kk + 4 + jj] : wv[4 * kk + jj]) + __shfl_xor_sync(0xffffffffu, wv[4 * kk + 2 + jj], 16);
                }
                {
                    const uint32_t sA = sb + (ci >> 1) * B_STAGE + ((ci & 1) * 2 + cw) * 8192;
#pragma unroll
                    for (int kk = 0; kk < 8; kk++) {
                        const float keep = podd ? f[2 * kk + 1] : f[2 * kk];
                        const float recv = __shfl_xor_sync(0xffffffffu, podd ? f[2 * kk] : f[2 * kk + 1], 4);
                        const uint32_t yw = pack_bf2(podd ? recv : keep, podd ? keep : recv);
                        asm volatile("st.shared.b32 [%0], %1;" :: "r"(sA + w * 1024 + (32 * kk + 8 * (r >> 1) + 2 * c4 + podd) * 4), "r"(yw) : "memory");
                    }
                }
                if (lane == 0 && ci == 1) H3_TR(3, (cw * 4 + w) * 16 + 13);
                if (ci < 3) {
                    uint32_t hx[8];
                    conv_frag_addr(hx, sb + ((ci + 1) >> 1) * B_STAGE + (((ci + 1) & 1) * 2 + cw) * 8192 + cpy, w0, xb);
                    conv_load_a<0>(a, hx);
                    a[0][0] &= mask0;
                }
                if (lane == 0 && ci == 1) H3_TR(3, (cw * 4 + w) * 16 + 14);
            }
            bar_sync(1 + cw, 128);
            conv_finish(3);
            conv_store(3);
            if (lane == 0) bulk_wait_read();
            bar_sync(1 + cw, 128);
            if (wtid < 2) mbar_arrive_cta(bars + BAR_EMPTYB + 8 * ST_U, wtid);
            if (tid == 128) H3_STAMP(11);
        }
        {
            float acc[64];
            const int srow = m2 * 128 + cw * 64 + w * 16 + (lane >> 2);
            const uint2 st0 = __ldcg(p.stats + srow), st1 = __ldcg(p.stats + srow + 8);
            int i6 = 0, prev = 0; uint32_t rho = 0;
#pragma unroll 1
            for (int kb = 0; kb < 56; kb++) {
                const int sg = (0x512034 >> (4 * i6)) & 15;
                mbar_wait(bars + BAR_FULLB + 8 * sg, ((0x21u >> i6) & 1u) ^ rho);
                if (wtid == 0) H3_TR(2, cw * 128 + kb * 2);
                if (tid == 128) { if (kb == 0) H3_STAMP(28); if (kb == 8) H3_STAMP(10); if (kb == 16) H3_STAMP(16); if (kb == 32) H3_STAMP(26); if (kb == 44) H3_STAMP(27); }
                const uint64_t da = descA + sg * (B_STAGE >> 4), db = descB + sg * (B_STAGE >> 4);
                wg_fence();
                wgmma_128(acc, da, db, kb != 0);
#pragma unroll
                for (int k = 1; k < 4; k++) wgmma_128(acc, da + k * 2, db + k * 128, 1);
                wg_commit();
                                if (kb == 8 && lane == 0) { bulk_wait_all(); flag_add_after_bulk(p.flags + (FL_Y + (cta >> 4)) * FLAG_STRIDE); }
                wg_wait<1>();
                if (wtid == 0) H3_TR(2, cw * 128 + kb * 2 + 1);
                if (kb > 0 && wtid < 2) mbar_arrive_cta(bars + BAR_EMPTYB + 8 * prev, wtid);
                prev = sg;
                if (++i6 == 6) { i6 = 0; rho ^= 1; }
            }
            mbar_wait(bars + BAR_OPFULL, 0);
            wg_wait<0>();
            if (tid == 128) H3_STAMP(12);
            mbar_wait(bars + BAR_FULLB + 0, 1);
            if (tid == 128) H3_STAMP(20);
            const float inv0 = __uint_as_float(st0.y), inv1 = __uint_as_float(st1.y);
            const uint32_t ycol = sb + OFF_STG + cw * 16384 + (((7 - 2 * w - ((lane >> 3) & 1)) ^ lrow7) << 4) + lrow7 * 128;
            const uint32_t xrow = sb + (cw * 64 + lrow) * 128;
#pragma unroll 1
            for (int g2 = 0; g2 < 2; g2++) {
#pragma unroll
                for (int hh = 0; hh < 4; hh++) {
                    const uint32_t grp = hh * 2 + lgrp;
                    const uint32_t xa = xrow + g2 * 16384 + ((grp ^ lrow7) << 4);
                    uint32_t x[4], y[4], o[4];
                    ldsm_x4(xa, x[0], x[1], x[2], x[3]);
                    ldsm_x4_t(ycol + (g2 * 8 + grp) * 1024, y[0], y[1], y[2], y[3]);
#pragma unroll
                    for (int i = 0; i < 4; i++) {
                        const uint32_t dd = bf2_sub(x[i], (i & 1) ? st1.x : st0.x);
                        const float iv = (i & 1) ? inv1 : inv0;
                        const uint32_t xn = pack_bf2(bf_lo(dd) * iv, bf_hi(dd) * iv);
                        o[i] = bf2_add(x[i], bf2_mul(bf2_mul(xn, y[i]), silu_bf2(pack_bf2(acc[8 * hh + 2 * i], acc[8 * hh + 2 * i + 1]))));
                    }
                    stsm_x4(xa, o[0], o[1], o[2], o[3]);
                }
#pragma unroll
                for (int i = 0; i < 32; i++) acc[i] = acc[i + 32];
                fence_async_smem();
                bar_sync(1 + cw, 128);
                if (wtid == 0) { tma_store_2d(&p.tmOut64, sb + g2 * 16384 + cw * 8192, n2 + g2 * 64, m2 * 128 + cw * 64); bulk_commit(); }
            }
            if (tid == 128) H3_STAMP(21);
            if (wtid == 0) bulk_wait_read();
            if (tid == 128) { H3_STAMP(13); H3_GSTAMP(31); }
        }
        cluster_sync();
    }
}

typedef CUresult (*EncodeTiledFn)(CUtensorMap*, CUtensorMapDataType, cuuint32_t, void*, const cuuint64_t*, const cuuint64_t*,
                                  const cuuint32_t*, const cuuint32_t*, CUtensorMapInterleave, CUtensorMapSwizzle,
                                  CUtensorMapL2promotion, CUtensorMapFloatOOBfill);

static void make_map(EncodeTiledFn enc, CUtensorMap* m, const void* ptr, int rank, const uint64_t* dims, const uint64_t* strides, const uint32_t* box,
                     CUtensorMapSwizzle swz = CU_TENSOR_MAP_SWIZZLE_128B) {
    cuuint64_t d[3], s[2];
    cuuint32_t b[3], es[3] = {1, 1, 1};
    for (int i = 0; i < rank; i++) { d[i] = dims[i]; b[i] = box[i]; }
    for (int i = 0; i + 1 < rank; i++) s[i] = strides[i];
    CUresult r = enc(m, CU_TENSOR_MAP_DATA_TYPE_BFLOAT16, rank, const_cast<void*>(ptr), d, s, b, es, CU_TENSOR_MAP_INTERLEAVE_NONE,
                     swz, CU_TENSOR_MAP_L2_PROMOTION_L2_128B, CU_TENSOR_MAP_FLOAT_OOB_FILL_NONE);
    if (r != CUDA_SUCCESS) fprintf(stderr, "cuTensorMapEncodeTiled failed: %d\n", (int)r);
}
static void map2d(EncodeTiledFn enc, CUtensorMap* m, const void* ptr, uint64_t cols, uint64_t rows, uint32_t box_rows) {
    const uint64_t d[2] = {cols, rows}, s[1] = {cols * 2};
    const uint32_t b[2] = {64, box_rows};
    make_map(enc, m, ptr, 2, d, s, b);
}
static void map3d(EncodeTiledFn enc, CUtensorMap* m, const void* ptr, uint64_t cols, uint64_t rows, uint32_t groups) {
    const uint64_t d[3] = {64, rows, cols / 64}, s[2] = {cols * 2, 128};
    const uint32_t b[3] = {64, 64, groups};
    make_map(enc, m, ptr, 3, d, s, b);
}

static long long* g_dbg_ptr = nullptr;

}

extern "C" void kernel_launch(void* const* d_in, const int* in_sizes, int n_in, void* d_out, int out_size) {
    using namespace h3;
    (void)in_sizes; (void)n_in; (void)out_size;
    static EncodeTiledFn enc = nullptr;
    static void *xn, *kvT, *hbuf, *y2T, *flags, *stats;
    if (!enc) {
        void* fn = nullptr;
        cudaDriverEntryPointQueryResult qr;
        cudaGetDriverEntryPoint("cuTensorMapEncodeTiled", &fn, cudaEnableDefault, &qr);
        enc = (EncodeTiledFn)fn;
        cudaGetSymbolAddress(&xn, g_xn);
        cudaGetSymbolAddress(&kvT, g_kvT);
        cudaGetSymbolAddress(&hbuf, g_h);
        cudaGetSymbolAddress(&y2T, g_y2T);
        cudaGetSymbolAddress(&flags, g_flags);
        cudaGetSymbolAddress(&stats, g_stats);
        cudaFuncSetAttribute(h3_kernel, cudaFuncAttributeMaxDynamicSharedMemorySize, SMEM_BYTES);
    }
    Params p;
    const bf16* q = (const bf16*)d_in[0];
    p.q = q; p.k = (const bf16*)d_in[1]; p.v = (const bf16*)d_in[2];
    p.shift_k = (const bf16*)d_in[3]; p.ssm_k = (const bf16*)d_in[4]; p.ssm_D = (const bf16*)d_in[5];
    const bf16* wg = (const bf16*)d_in[7];
    const bf16* wu = (const bf16*)d_in[8];
    const bf16* wd = (const bf16*)d_in[9];
    p.xn = (bf16*)xn; p.kvT = (bf16*)kvT; p.y2T = (bf16*)y2T; p.flags = (unsigned*)flags; p.stats = (uint2*)stats;
    p.dbg = g_dbg_ptr;
    map2d(enc, &p.tmXn128, xn, D, S, 128);
    map2d(enc, &p.tmXn64, xn, D, S, 64);
    map3d(enc, &p.tmWg2, wg, F, D, 2);
    map3d(enc, &p.tmWu2, wu, F, D, 2);
    map3d(enc, &p.tmWg1, wg, F, D, 1);
    map3d(enc, &p.tmWu1, wu, F, D, 1);
    map2d(enc, &p.tmH64, hbuf, F, S, 64);
    map3d(enc, &p.tmWd, wd, D, F, 2);
    map2d(enc, &p.tmX128, q, D, S, 128);
    map2d(enc, &p.tmY2T, y2T, S, D, 128);
    map2d(enc, &p.tmOut64, d_out, D, S, 64);
    {
        const uint64_t d[2] = {D, S}, st[1] = {D * 2};
        const uint32_t bk[2] = {128, 67}, bv[2] = {128, 64};
        make_map(enc, &p.tmK, p.k, 2, d, st, bk, CU_TENSOR_MAP_SWIZZLE_NONE);
        make_map(enc, &p.tmV, p.v, 2, d, st, bv, CU_TENSOR_MAP_SWIZZLE_NONE);
    }
    map2d(enc, &p.tmKvT, kvT, S, D, 128);

    cudaLaunchConfig_t cfg = {};
    cfg.gridDim = dim3(NCTA + 4);
    cfg.blockDim = dim3(384);
    cfg.dynamicSmemBytes = SMEM_BYTES;
    cfg.stream = cudaStreamPerThread;
    cudaLaunchAttribute at[1];
    at[0].id = cudaLaunchAttributeClusterDimension;
    at[0].val.clusterDim.x = 2; at[0].val.clusterDim.y = 1; at[0].val.clusterDim.z = 1;
    cfg.attrs = at; cfg.numAttrs = 1;
    cudaLaunchKernelEx(&cfg, h3_kernel, p);
}
```

```cpp
#include <cuda_runtime.h>
#include <cuda_bf16.h>
#include <cuda.h>
#include <stdint.h>
#include <stdio.h>

namespace h3 {

typedef __nv_bfloat16 bf16;

constexpr int S = 2048;
constexpr int D = 1024;
constexpr int F = 3584;
constexpr int NCTA = 128;

__device__ __align__(1024) bf16 g_xn[S * D];
__device__ __align__(1024) bf16 g_kvT[D * S];
__device__ __align__(1024) bf16 g_h[S * F];
__device__ __align__(1024) bf16 g_y2T[D * S];
__device__ __align__(1024) uint2 g_stats[S];
constexpr int FLAG_STRIDE = 32;
constexpr int FL_XN = 0, FL_H = 16, FL_Y = 32, FL_KV = 40, FL_DONE = 41, FL_H2 = 42, FL_COUNT = 58;
__device__ __align__(1024) unsigned g_flags[FL_COUNT * FLAG_STRIDE];

struct alignas(64) Params {
    CUtensorMap tmXn128;
    CUtensorMap tmXn64;
    CUtensorMap tmWg2;
    CUtensorMap tmWu2;
    CUtensorMap tmWg1;
    CUtensorMap tmWu1;
    CUtensorMap tmH64;
    CUtensorMap tmWd;
    CUtensorMap tmX128;
    CUtensorMap tmY2T;
    CUtensorMap tmOut64;
    CUtensorMap tmK;
    CUtensorMap tmV;
    CUtensorMap tmKvT;
    const bf16* q; const bf16* k; const bf16* v; const bf16* shift_k; const bf16* ssm_k; const bf16* ssm_D;
    bf16* xn; bf16* kvT; bf16* y2T; uint2* stats;
    unsigned* flags;
    long long* dbg;
};

constexpr uint32_t RING_BYTES = 196608;
constexpr uint32_t A_STAGE = 49152, B_STAGE = 32768;
constexpr uint32_t OFF_STG = RING_BYTES + 1024;
constexpr uint32_t OFF_BAR = OFF_STG + 32768;
constexpr uint32_t BAR_FULLA = 0, BAR_EMPTYA = 32, BAR_FULLB = 96, BAR_EMPTYB = 144,
                   BAR_STGFULL = 200, BAR_STGEMPTY = 208, BAR_ALTFULL = 216, BAR_OPFULL = 232,
                   BAR_ALT2FULL = 240, OFF_STAT = 256;
constexpr uint32_t SMEM_BYTES = OFF_BAR + 512 + 1024;

constexpr int ST_H = 4, ST_U = 5, ST_C0 = 0, ST_C1 = 1, ST_ALT = 2, ST_ALT2 = 3;
constexpr uint32_t U_PITCH = 4096 + 128;

__device__ __forceinline__ uint32_t smem_u32(const void* p) { return (uint32_t)__cvta_generic_to_shared(p); }
__device__ __forceinline__ uint64_t make_desc(uint32_t addr, uint32_t lbo, uint32_t sbo) {
    uint64_t d = (uint64_t)((addr & 0x3FFFF) >> 4);
    d |= (uint64_t)((lbo & 0x3FFFF) >> 4) << 16;
    d |= (uint64_t)((sbo & 0x3FFFF) >> 4) << 32;
    d |= (uint64_t)1 << 62;
    return d;
}
__device__ __forceinline__ uint64_t make_desc_noswz(uint32_t addr, uint32_t lbo, uint32_t sbo) {
    return (uint64_t)((addr & 0x3FFFF) >> 4) | ((uint64_t)(lbo >> 4) << 16) | ((uint64_t)(sbo >> 4) << 32);
}
constexpr uint32_t WAIT_LIMIT = 1u << 27;
__device__ __forceinline__ void mbar_init(uint32_t bar, uint32_t count) { asm volatile("mbarrier.init.shared::cta.b64 [%0], %1;" :: "r"(bar), "r"(count) : "memory"); }
__device__ __forceinline__ void mbar_expect_tx(uint32_t bar, uint32_t bytes) { asm volatile("mbarrier.arrive.expect_tx.shared::cta.b64 _, [%0], %1;" :: "r"(bar), "r"(bytes) : "memory"); }
__device__ __forceinline__ void mbar_arrive(uint32_t bar) { asm volatile("mbarrier.arrive.shared::cta.b64 _, [%0];" :: "r"(bar) : "memory"); }
__device__ __forceinline__ void mbar_arrive_cta(uint32_t bar, uint32_t cta) {
    asm volatile("{\n.reg .b32 ra;\nmapa.shared::cluster.u32 ra, %0, %1;\nmbarrier.arrive.shared::cluster.b64 _, [ra];\n}" :: "r"(bar), "r"(cta) : "memory");
}
__device__ __forceinline__ uint32_t mbar_try(uint32_t bar, uint32_t parity) {
    uint32_t ok;
    asm volatile("{\n.reg .pred p;\nmbarrier.try_wait.parity.shared::cta.b64 p, [%1], %2;\nselp.u32 %0, 1, 0, p;\n}" : "=r"(ok) : "r"(bar), "r"(parity) : "memory");
    return ok;
}
__device__ __forceinline__ void mbar_wait(uint32_t bar, uint32_t parity) {
    if (!mbar_try(bar, parity)) {
        const uint32_t t0 = (uint32_t)clock();
        while (!mbar_try(bar, parity) && (uint32_t)clock() - t0 < WAIT_LIMIT) {}
    }
}
__device__ __forceinline__ void mbar_wait_idle(uint32_t bar, uint32_t parity) {
    const uint32_t t0 = (uint32_t)clock();
    while (!mbar_try(bar, parity) && (uint32_t)clock() - t0 < WAIT_LIMIT) {
        __nanosleep(256);
    }
}
__device__ __forceinline__ void flag_wait(const unsigned* f, unsigned target) {
    const uint32_t t0 = (uint32_t)clock();
    unsigned v;
    do {
        asm volatile("ld.acquire.gpu.global.u32 %0, [%1];" : "=r"(v) : "l"(f) : "memory");
    } while (v < target && (uint32_t)clock() - t0 < WAIT_LIMIT);
}
__device__ __forceinline__ void flag_add_after_bulk(unsigned* f) {
    asm volatile("red.relaxed.gpu.global.add.u32 [%0], 1;" :: "l"(f) : "memory");
}
__device__ __forceinline__ void cluster_arrive() { asm volatile("barrier.cluster.arrive.relaxed;" ::: "memory"); }
__device__ __forceinline__ void cluster_wait() { asm volatile("barrier.cluster.wait.acquire;" ::: "memory"); }
__device__ __forceinline__ void tma_2d(uint32_t dst, const CUtensorMap* m, int c0, int c1, uint32_t bar) {
    asm volatile("cp.async.bulk.tensor.2d.shared::cluster.global.mbarrier::complete_tx::bytes [%0], [%1, {%3, %4}], [%2];"
        :: "r"(dst), "l"(m), "r"(bar), "r"(c0), "r"(c1) : "memory");
}
__device__ __forceinline__ void tma_2d_mc(uint32_t dst, const CUtensorMap* m, int c0, int c1, uint32_t bar) {
    asm volatile("cp.async.bulk.tensor.2d.shared::cluster.global.mbarrier::complete_tx::bytes.multicast::cluster [%0], [%1, {%3, %4}], [%2], %5;"
        :: "r"(dst), "l"(m), "r"(bar), "r"(c0), "r"(c1), "h"((uint16_t)3) : "memory");
}
__device__ __forceinline__ void tma_3d(uint32_t dst, const CUtensorMap* m, int c0, int c1, int c2, uint32_t bar) {
    asm volatile("cp.async.bulk.tensor.3d.shared::cluster.global.mbarrier::complete_tx::bytes [%0], [%1, {%3, %4, %5}], [%2];"
        :: "r"(dst), "l"(m), "r"(bar), "r"(c0), "r"(c1), "r"(c2) : "memory");
}
__device__ __forceinline__ uint64_t policy_evict_first() {
    uint64_t pol; asm volatile("createpolicy.fractional.L2::evict_first.b64 %0, 1.0;" : "=l"(pol)); return pol;
}
__device__ __forceinline__ void tma_3d_h(uint32_t dst, const CUtensorMap* m, int c0, int c1, int c2, uint32_t bar, uint64_t pol) {
    asm volatile("cp.async.bulk.tensor.3d.shared::cluster.global.mbarrier::complete_tx::bytes.L2::cache_hint [%0], [%1, {%3, %4, %5}], [%2], %6;"
        :: "r"(dst), "l"(m), "r"(bar), "r"(c0), "r"(c1), "r"(c2), "l"(pol) : "memory");
}
__device__ __forceinline__ void tma_2d_h(uint32_t dst, const CUtensorMap* m, int c0, int c1, uint32_t bar, uint64_t pol) {
    asm volatile("cp.async.bulk.tensor.2d.shared::cluster.global.mbarrier::complete_tx::bytes.L2::cache_hint [%0], [%1, {%3, %4}], [%2], %5;"
        :: "r"(dst), "l"(m), "r"(bar), "r"(c0), "r"(c1), "l"(pol) : "memory");
}
__device__ __forceinline__ void pf_bulk_h(const void* src, uint32_t bytes, uint64_t pol) {
    asm volatile("cp.async.bulk.prefetch.L2.global.L2::cache_hint [%0], %1, %2;" :: "l"(src), "r"(bytes), "l"(pol) : "memory");
}
__device__ __forceinline__ void tma_3d_mc_h(uint32_t dst, const CUtensorMap* m, int c0, int c1, int c2, uint32_t bar, uint64_t pol) {
    asm volatile("cp.async.bulk.tensor.3d.shared::cluster.global.mbarrier::complete_tx::bytes.multicast::cluster.L2::cache_hint [%0], [%1, {%3, %4, %5}], [%2], %6, %7;"
        :: "r"(dst), "l"(m), "r"(bar), "r"(c0), "r"(c1), "r"(c2), "h"((uint16_t)3), "l"(pol) : "memory");
}
__device__ __forceinline__ void bulk_g2s_h(uint32_t dst, const void* src, uint32_t bytes, uint32_t bar, uint64_t pol) {
    asm volatile("cp.async.bulk.shared::cluster.global.mbarrier::complete_tx::bytes.L2::cache_hint [%0], [%1], %2, [%3], %4;"
        :: "r"(dst), "l"(src), "r"(bytes), "r"(bar), "l"(pol) : "memory");
}
__device__ __forceinline__ void bulk_s2g(void* dst, uint32_t src, uint32_t bytes) {
    asm volatile("cp.async.bulk.global.shared::cta.bulk_group [%0], [%1], %2;" :: "l"(dst), "r"(src), "r"(bytes) : "memory");
}
__device__ __forceinline__ void tma_store_2d(const CUtensorMap* m, uint32_t src, int c0, int c1) {
    asm volatile("cp.async.bulk.tensor.2d.global.shared::cta.bulk_group [%0, {%2, %3}], [%1];"
        :: "l"(m), "r"(src), "r"(c0), "r"(c1) : "memory");
}
__device__ __forceinline__ void pf_2d(const CUtensorMap* m, int c0, int c1) {
    asm volatile("cp.async.bulk.prefetch.tensor.2d.L2.global.tile [%0, {%1, %2}];" :: "l"(m), "r"(c0), "r"(c1) : "memory");
}
__device__ __forceinline__ void pf_bulk(const void* src, uint32_t bytes) {
    asm volatile("cp.async.bulk.prefetch.L2.global [%0], %1;" :: "l"(src), "r"(bytes) : "memory");
}
__device__ __forceinline__ void bulk_commit() { asm volatile("cp.async.bulk.commit_group;" ::: "memory"); }
__device__ __forceinline__ void bulk_wait_read() { asm volatile("cp.async.bulk.wait_group.read 0;" ::: "memory"); }
__device__ __forceinline__ void bulk_wait_all() { asm volatile("cp.async.bulk.wait_group 0;" ::: "memory"); }
__device__ __forceinline__ void fence_async_smem() { asm volatile("fence.proxy.async.shared::cta;" ::: "memory"); }
__device__ __forceinline__ void bar_sync(int id, int n) { asm volatile("bar.sync %0, %1;" :: "r"(id), "r"(n) : "memory"); }
__device__ __forceinline__ void bar_arrive(int id, int n) { asm volatile("bar.arrive %0, %1;" :: "r"(id), "r"(n) : "memory"); }
__device__ __forceinline__ void cluster_sync() {
    asm volatile("barrier.cluster.arrive.release.aligned;" ::: "memory");
    asm volatile("barrier.cluster.wait.acquire.aligned;" ::: "memory");
}
__device__ __forceinline__ void wg_fence() { asm volatile("wgmma.fence.sync.aligned;" ::: "memory"); }
__device__ __forceinline__ void wg_commit() { asm volatile("wgmma.commit_group.sync.aligned;" ::: "memory"); }
template <int N> __device__ __forceinline__ void wg_wait() { asm volatile("wgmma.wait_group.sync.aligned %0;" :: "n"(N) : "memory"); }

#define H3_R4(b)  "+f"(d[b+0]), "+f"(d[b+1]), "+f"(d[b+2]), "+f"(d[b+3])
#define H3_R8(b)  H3_R4(b), H3_R4(b+4)
#define H3_R16(b) H3_R8(b), H3_R8(b+8)
#define H3_R32(b) H3_R16(b), H3_R16(b+16)
#define H3_R64(b) H3_R32(b), H3_R32(b+32)

__device__ __forceinline__ void wgmma_256(float (&d)[128], uint64_t a, uint64_t b, int scale_d) {
    asm volatile("{\n.reg .pred p;\nsetp.ne.b32 p, %130, 0;\n"
    "wgmma.mma_async.sync.aligned.m64n256k16.f32.bf16.bf16 "
    "{%0,%1,%2,%3,%4,%5,%6,%7,%8,%9,%10,%11,%12,%13,%14,%15,"
    "%16,%17,%18,%19,%20,%21,%22,%23,%24,%25,%26,%27,%28,%29,%30,%31,"
    "%32,%33,%34,%35,%36,%37,%38,%39,%40,%41,%42,%43,%44,%45,%46,%47,"
    "%48,%49,%50,%51,%52,%53,%54,%55,%56,%57,%58,%59,%60,%61,%62,%63,"
    "%64,%65,%66,%67,%68,%69,%70,%71,%72,%73,%74,%75,%76,%77,%78,%79,"
    "%80,%81,%82,%83,%84,%85,%86,%87,%88,%89,%90,%91,%92,%93,%94,%95,"
    "%96,%97,%98,%99,%100,%101,%102,%103,%104,%105,%106,%107,%108,%109,%110,%111,"
    "%112,%113,%114,%115,%116,%117,%118,%119,%120,%121,%122,%123,%124,%125,%126,%127},"
    "%128, %129, p, 1, 1, 0, 1;\n}\n"
    : H3_R64(0), H3_R64(64)
    : "l"(a), "l"(b), "r"(scale_d));
}
__device__ __forceinline__ void wgmma_128(float (&d)[64], uint64_t a, uint64_t b, int scale_d) {
    asm volatile("{\n.reg .pred p;\nsetp.ne.b32 p, %66, 0;\n"
    "wgmma.mma_async.sync.aligned.m64n128k16.f32.bf16.bf16 "
    "{%0,%1,%2,%3,%4,%5,%6,%7,%8,%9,%10,%11,%12,%13,%14,%15,"
    "%16,%17,%18,%19,%20,%21,%22,%23,%24,%25,%26,%27,%28,%29,%30,%31,"
    "%32,%33,%34,%35,%36,%37,%38,%39,%40,%41,%42,%43,%44,%45,%46,%47,"
    "%48,%49,%50,%51,%52,%53,%54,%55,%56,%57,%58,%59,%60,%61,%62,%63},"
    "%64, %65, p, 1, 1, 0, 1;\n}\n"
    : H3_R64(0)
    : "l"(a), "l"(b), "r"(scale_d));
}
__device__ __forceinline__ void ldsm_x4(uint32_t addr, uint32_t& r0, uint32_t& r1, uint32_t& r2, uint32_t& r3) {
    asm volatile("ldmatrix.sync.aligned.m8n8.x4.shared.b16 {%0,%1,%2,%3}, [%4];" : "=r"(r0), "=r"(r1), "=r"(r2), "=r"(r3) : "r"(addr) : "memory");
}
__device__ __forceinline__ void ldsm_x4_t(uint32_t addr, uint32_t& r0, uint32_t& r1, uint32_t& r2, uint32_t& r3) {
    asm volatile("ldmatrix.sync.aligned.m8n8.x4.trans.shared.b16 {%0,%1,%2,%3}, [%4];" : "=r"(r0), "=r"(r1), "=r"(r2), "=r"(r3) : "r"(addr) : "memory");
}
__device__ __forceinline__ void stsm_x4(uint32_t addr, uint32_t r0, uint32_t r1, uint32_t r2, uint32_t r3) {
    asm volatile("stmatrix.sync.aligned.m8n8.x4.shared.b16 [%0], {%1,%2,%3,%4};" :: "r"(addr), "r"(r0), "r"(r1), "r"(r2), "r"(r3) : "memory");
}
template <int OFF> __device__ __forceinline__ uint32_t lds32_o(uint32_t addr) { uint32_t v; asm volatile("ld.shared.b32 %0, [%1+%2];" : "=r"(v) : "r"(addr), "n"(OFF) : "memory"); return v; }
__device__ __forceinline__ uint32_t lds32(uint32_t addr) { uint32_t v; asm volatile("ld.shared.b32 %0, [%1];" : "=r"(v) : "r"(addr) : "memory"); return v; }
__device__ __forceinline__ uint4 lds128(uint32_t addr) { uint4 v; asm volatile("ld.shared.v4.b32 {%0,%1,%2,%3}, [%4];" : "=r"(v.x), "=r"(v.y), "=r"(v.z), "=r"(v.w) : "r"(addr) : "memory"); return v; }
__device__ __forceinline__ void sts128(uint32_t addr, uint32_t a, uint32_t b, uint32_t c, uint32_t d) { asm volatile("st.shared.v4.b32 [%0], {%1,%2,%3,%4};" :: "r"(addr), "r"(a), "r"(b), "r"(c), "r"(d) : "memory"); }

__device__ __forceinline__ uint32_t bf2_mul(uint32_t a, uint32_t b) { uint32_t r; asm("mul.rn.bf16x2 %0, %1, %2;" : "=r"(r) : "r"(a), "r"(b)); return r; }
__device__ __forceinline__ uint32_t bf2_add(uint32_t a, uint32_t b) { uint32_t r; asm("add.rn.bf16x2 %0, %1, %2;" : "=r"(r) : "r"(a), "r"(b)); return r; }
__device__ __forceinline__ uint32_t bf2_sub(uint32_t a, uint32_t b) { uint32_t r; asm("sub.rn.bf16x2 %0, %1, %2;" : "=r"(r) : "r"(a), "r"(b)); return r; }
__device__ __forceinline__ uint32_t pack_bf2(float lo, float hi) { uint32_t r; asm("cvt.rn.bf16x2.f32 %0, %1, %2;" : "=r"(r) : "f"(hi), "f"(lo)); return r; }
__device__ __forceinline__ float bf_lo(uint32_t v) { return __uint_as_float(v << 16); }
__device__ __forceinline__ float bf_hi(uint32_t v) { return __uint_as_float(v & 0xFFFF0000u); }
__device__ __forceinline__ float silu_f(float x) {
    float e, r;
    asm("ex2.approx.ftz.f32 %0, %1;" : "=f"(e) : "f"(x * -1.4426950408889634f));
    asm("rcp.approx.ftz.f32 %0, %1;" : "=f"(r) : "f"(1.0f + e));
    return x * r;
}
__device__ __forceinline__ uint32_t silu_bf2(uint32_t v) { return pack_bf2(silu_f(bf_lo(v)), silu_f(bf_hi(v))); }

#define H3_TR(ph, i) do {} while (0)
#define H3_STAMP(i) do {} while (0)
#define H3_GSTAMP(i) do {} while (0)

template <int I>
__device__ __forceinline__ void stage_piece(const uint32_t (&pg)[32], const uint32_t (&pu)[32], uint32_t stg_lane, uint32_t lrow7, uint32_t lgrp) {
    const uint32_t addr = stg_lane + (((2 * (I & 3) + lgrp) ^ lrow7) << 4);
    stsm_x4(addr, pg[4 * I], pg[4 * I + 1], pg[4 * I + 2], pg[4 * I + 3]);
    stsm_x4(addr + 8192, pu[4 * I], pu[4 * I + 1], pu[4 * I + 2], pu[4 * I + 3]);
}
__device__ __forceinline__ void stage_piece_dyn(int i, const uint32_t (&pg)[32], const uint32_t (&pu)[32], uint32_t stg_lane, uint32_t lrow7, uint32_t lgrp) {
    switch (i) {
        case 0: stage_piece<0>(pg, pu, stg_lane, lrow7, lgrp); break;
        case 1: stage_piece<1>(pg, pu, stg_lane, lrow7, lgrp); break;
        case 2: stage_piece<2>(pg, pu, stg_lane, lrow7, lgrp); break;
        case 3: stage_piece<3>(pg, pu, stg_lane, lrow7, lgrp); break;
        case 4: stage_piece<4>(pg, pu, stg_lane, lrow7, lgrp); break;
        case 5: stage_piece<5>(pg, pu, stg_lane, lrow7, lgrp); break;
        case 6: stage_piece<6>(pg, pu, stg_lane, lrow7, lgrp); break;
        default: stage_piece<7>(pg, pu, stg_lane, lrow7, lgrp); break;
    }
}
__device__ __forceinline__ void wgmma_128_lo(float (&d)[128], uint64_t a, uint64_t b, int scale_d) {
    asm volatile("{\n.reg .pred p;\nsetp.ne.b32 p, %66, 0;\n"
    "wgmma.mma_async.sync.aligned.m64n128k16.f32.bf16.bf16 "
    "{%0,%1,%2,%3,%4,%5,%6,%7,%8,%9,%10,%11,%12,%13,%14,%15,"
    "%16,%17,%18,%19,%20,%21,%22,%23,%24,%25,%26,%27,%28,%29,%30,%31,"
    "%32,%33,%34,%35,%36,%37,%38,%39,%40,%41,%42,%43,%44,%45,%46,%47,"
    "%48,%49,%50,%51,%52,%53,%54,%55,%56,%57,%58,%59,%60,%61,%62,%63},"
    "%64, %65, p, 1, 1, 0, 1;\n}\n"
    : H3_R64(0)
    : "l"(a), "l"(b), "r"(scale_d));
}

template <int N> __device__ __forceinline__ void wgmma_rs(float (&d)[128], const uint32_t (&a)[4], uint64_t b, int scale_d);
template <> __device__ __forceinline__ void wgmma_rs<64>(float (&d)[128], const uint32_t (&a)[4], uint64_t b, int scale_d) {
    asm volatile("{\n.reg .pred p;\nsetp.ne.b32 p, %37, 0;\nwgmma.mma_async.sync.aligned.m64n64k16.f32.bf16.bf16 {%0,%1,%2,%3,%4,%5,%6,%7,%8,%9,%10,%11,%12,%13,%14,%15,%16,%17,%18,%19,%20,%21,%22,%23,%24,%25,%26,%27,%28,%29,%30,%31}, {%32,%33,%34,%35}, %36, p, 1, 1, 0;\n}\n"
        : "+f"(d[0]), "+f"(d[1]), "+f"(d[2]), "+f"(d[3]), "+f"(d[4]), "+f"(d[5]), "+f"(d[6]), "+f"(d[7]), "+f"(d[8]), "+f"(d[9]), "+f"(d[10]), "+f"(d[11]), "+f"(d[12]), "+f"(d[13]), "+f"(d[14]), "+f"(d[15]), "+f"(d[16]), "+f"(d[17]), "+f"(d[18]), "+f"(d[19]), "+f"(d[20]), "+f"(d[21]), "+f"(d[22]), "+f"(d[23]), "+f"(d[24]), "+f"(d[25]), "+f"(d[26]), "+f"(d[27]), "+f"(d[28]), "+f"(d[29]), "+f"(d[30]), "+f"(d[31])
        : "r"(a[0]), "r"(a[1]), "r"(a[2]), "r"(a[3]), "l"(b), "r"(scale_d));
}
template <> __device__ __forceinline__ void wgmma_rs<128>(float (&d)[128], const uint32_t (&a)[4], uint64_t b, int scale_d) {
    asm volatile("{\n.reg .pred p;\nsetp.ne.b32 p, %69, 0;\nwgmma.mma_async.sync.aligned.m64n128k16.f32.bf16.bf16 {%0,%1,%2,%3,%4,%5,%6,%7,%8,%9,%10,%11,%12,%13,%14,%15,%16,%17,%18,%19,%20,%21,%22,%23,%24,%25,%26,%27,%28,%29,%30,%31,%32,%33,%34,%35,%36,%37,%38,%39,%40,%41,%42,%43,%44,%45,%46,%47,%48,%49,%50,%51,%52,%53,%54,%55,%56,%57,%58,%59,%60,%61,%62,%63}, {%64,%65,%66,%67}, %68, p, 1, 1, 0;\n}\n"
        : "+f"(d[0]), "+f"(d[1]), "+f"(d[2]), "+f"(d[3]), "+f"(d[4]), "+f"(d[5]), "+f"(d[6]), "+f"(d[7]), "+f"(d[8]), "+f"(d[9]), "+f"(d[10]), "+f"(d[11]), "+f"(d[12]), "+f"(d[13]), "+f"(d[14]), "+f"(d[15]), "+f"(d[16]), "+f"(d[17]), "+f"(d[18]), "+f"(d[19]), "+f"(d[20]), "+f"(d[21]), "+f"(d[22]), "+f"(d[23]), "+f"(d[24]), "+f"(d[25]), "+f"(d[26]), "+f"(d[27]), "+f"(d[28]), "+f"(d[29]), "+f"(d[30]), "+f"(d[31]), "+f"(d[32]), "+f"(d[33]), "+f"(d[34]), "+f"(d[35]), "+f"(d[36]), "+f"(d[37]), "+f"(d[38]), "+f"(d[39]), "+f"(d[40]), "+f"(d[41]), "+f"(d[42]), "+f"(d[43]), "+f"(d[44]), "+f"(d[45]), "+f"(d[46]), "+f"(d[47]), "+f"(d[48]), "+f"(d[49]), "+f"(d[50]), "+f"(d[51]), "+f"(d[52]), "+f"(d[53]), "+f"(d[54]), "+f"(d[55]), "+f"(d[56]), "+f"(d[57]), "+f"(d[58]), "+f"(d[59]), "+f"(d[60]), "+f"(d[61]), "+f"(d[62]), "+f"(d[63])
        : "r"(a[0]), "r"(a[1]), "r"(a[2]), "r"(a[3]), "l"(b), "r"(scale_d));
}
template <> __device__ __forceinline__ void wgmma_rs<192>(float (&d)[128], const uint32_t (&a)[4], uint64_t b, int scale_d) {
    asm volatile("{\n.reg .pred p;\nsetp.ne.b32 p, %101, 0;\nwgmma.mma_async.sync.aligned.m64n192k16.f32.bf16.bf16 {%0,%1,%2,%3,%4,%5,%6,%7,%8,%9,%10,%11,%12,%13,%14,%15,%16,%17,%18,%19,%20,%21,%22,%23,%24,%25,%26,%27,%28,%29,%30,%31,%32,%33,%34,%35,%36,%37,%38,%39,%40,%41,%42,%43,%44,%45,%46,%47,%48,%49,%50,%51,%52,%53,%54,%55,%56,%57,%58,%59,%60,%61,%62,%63,%64,%65,%66,%67,%68,%69,%70,%71,%72,%73,%74,%75,%76,%77,%78,%79,%80,%81,%82,%83,%84,%85,%86,%87,%88,%89,%90,%91,%92,%93,%94,%95}, {%96,%97,%98,%99}, %100, p, 1, 1, 0;\n}\n"
        : "+f"(d[0]), "+f"(d[1]), "+f"(d[2]), "+f"(d[3]), "+f"(d[4]), "+f"(d[5]), "+f"(d[6]), "+f"(d[7]), "+f"(d[8]), "+f"(d[9]), "+f"(d[10]), "+f"(d[11]), "+f"(d[12]), "+f"(d[13]), "+f"(d[14]), "+f"(d[15]), "+f"(d[16]), "+f"(d[17]), "+f"(d[18]), "+f"(d[19]), "+f"(d[20]), "+f"(d[21]), "+f"(d[22]), "+f"(d[23]), "+f"(d[24]), "+f"(d[25]), "+f"(d[26]), "+f"(d[27]), "+f"(d[28]), "+f"(d[29]), "+f"(d[30]), "+f"(d[31]), "+f"(d[32]), "+f"(d[33]), "+f"(d[34]), "+f"(d[35]), "+f"(d[36]), "+f"(d[37]), "+f"(d[38]), "+f"(d[39]), "+f"(d[40]), "+f"(d[41]), "+f"(d[42]), "+f"(d[43]), "+f"(d[44]), "+f"(d[45]), "+f"(d[46]), "+f"(d[47]), "+f"(d[48]), "+f"(d[49]), "+f"(d[50]), "+f"(d[51]), "+f"(d[52]), "+f"(d[53]), "+f"(d[54]), "+f"(d[55]), "+f"(d[56]), "+f"(d[57]), "+f"(d[58]), "+f"(d[59]), "+f"(d[60]), "+f"(d[61]), "+f"(d[62]), "+f"(d[63]), "+f"(d[64]), "+f"(d[65]), "+f"(d[66]), "+f"(d[67]), "+f"(d[68]), "+f"(d[69]), "+f"(d[70]), "+f"(d[71]), "+f"(d[72]), "+f"(d[73]), "+f"(d[74]), "+f"(d[75]), "+f"(d[76]), "+f"(d[77]), "+f"(d[78]), "+f"(d[79]), "+f"(d[80]), "+f"(d[81]), "+f"(d[82]), "+f"(d[83]), "+f"(d[84]), "+f"(d[85]), "+f"(d[86]), "+f"(d[87]), "+f"(d[88]), "+f"(d[89]), "+f"(d[90]), "+f"(d[91]), "+f"(d[92]), "+f"(d[93]), "+f"(d[94]), "+f"(d[95])
        : "r"(a[0]), "r"(a[1]), "r"(a[2]), "r"(a[3]), "l"(b), "r"(scale_d));
}
template <> __device__ __forceinline__ void wgmma_rs<256>(float (&d)[128], const uint32_t (&a)[4], uint64_t b, int scale_d) {
    asm volatile("{\n.reg .pred p;\nsetp.ne.b32 p, %133, 0;\nwgmma.mma_async.sync.aligned.m64n256k16.f32.bf16.bf16 {%0,%1,%2,%3,%4,%5,%6,%7,%8,%9,%10,%11,%12,%13,%14,%15,%16,%17,%18,%19,%20,%21,%22,%23,%24,%25,%26,%27,%28,%29,%30,%31,%32,%33,%34,%35,%36,%37,%38,%39,%40,%41,%42,%43,%44,%45,%46,%47,%48,%49,%50,%51,%52,%53,%54,%55,%56,%57,%58,%59,%60,%61,%62,%63,%64,%65,%66,%67,%68,%69,%70,%71,%72,%73,%74,%75,%76,%77,%78,%79,%80,%81,%82,%83,%84,%85,%86,%87,%88,%89,%90,%91,%92,%93,%94,%95,%96,%97,%98,%99,%100,%101,%102,%103,%104,%105,%106,%107,%108,%109,%110,%111,%112,%113,%114,%115,%116,%117,%118,%119,%120,%121,%122,%123,%124,%125,%126,%127}, {%128,%129,%130,%131}, %132, p, 1, 1, 0;\n}\n"
        : "+f"(d[0]), "+f"(d[1]), "+f"(d[2]), "+f"(d[3]), "+f"(d[4]), "+f"(d[5]), "+f"(d[6]), "+f"(d[7]), "+f"(d[8]), "+f"(d[9]), "+f"(d[10]), "+f"(d[11]), "+f"(d[12]), "+f"(d[13]), "+f"(d[14]), "+f"(d[15]), "+f"(d[16]), "+f"(d[17]), "+f"(d[18]), "+f"(d[19]), "+f"(d[20]), "+f"(d[21]), "+f"(d[22]), "+f"(d[23]), "+f"(d[24]), "+f"(d[25]), "+f"(d[26]), "+f"(d[27]), "+f"(d[28]), "+f"(d[29]), "+f"(d[30]), "+f"(d[31]), "+f"(d[32]), "+f"(d[33]), "+f"(d[34]), "+f"(d[35]), "+f"(d[36]), "+f"(d[37]), "+f"(d[38]), "+f"(d[39]), "+f"(d[40]), "+f"(d[41]), "+f"(d[42]), "+f"(d[43]), "+f"(d[44]), "+f"(d[45]), "+f"(d[46]), "+f"(d[47]), "+f"(d[48]), "+f"(d[49]), "+f"(d[50]), "+f"(d[51]), "+f"(d[52]), "+f"(d[53]), "+f"(d[54]), "+f"(d[55]), "+f"(d[56]), "+f"(d[57]), "+f"(d[58]), "+f"(d[59]), "+f"(d[60]), "+f"(d[61]), "+f"(d[62]), "+f"(d[63]), "+f"(d[64]), "+f"(d[65]), "+f"(d[66]), "+f"(d[67]), "+f"(d[68]), "+f"(d[69]), "+f"(d[70]), "+f"(d[71]), "+f"(d[72]), "+f"(d[73]), "+f"(d[74]), "+f"(d[75]), "+f"(d[76]), "+f"(d[77]), "+f"(d[78]), "+f"(d[79]), "+f"(d[80]), "+f"(d[81]), "+f"(d[82]), "+f"(d[83]), "+f"(d[84]), "+f"(d[85]), "+f"(d[86]), "+f"(d[87]), "+f"(d[88]), "+f"(d[89]), "+f"(d[90]), "+f"(d[91]), "+f"(d[92]), "+f"(d[93]), "+f"(d[94]), "+f"(d[95]), "+f"(d[96]), "+f"(d[97]), "+f"(d[98]), "+f"(d[99]), "+f"(d[100]), "+f"(d[101]), "+f"(d[102]), "+f"(d[103]), "+f"(d[104]), "+f"(d[105]), "+f"(d[106]), "+f"(d[107]), "+f"(d[108]), "+f"(d[109]), "+f"(d[110]), "+f"(d[111]), "+f"(d[112]), "+f"(d[113]), "+f"(d[114]), "+f"(d[115]), "+f"(d[116]), "+f"(d[117]), "+f"(d[118]), "+f"(d[119]), "+f"(d[120]), "+f"(d[121]), "+f"(d[122]), "+f"(d[123]), "+f"(d[124]), "+f"(d[125]), "+f"(d[126]), "+f"(d[127])
        : "r"(a[0]), "r"(a[1]), "r"(a[2]), "r"(a[3]), "l"(b), "r"(scale_d));
}

template <int I> __device__ __forceinline__ void conv_load_a(uint32_t (&a)[16][4], const uint32_t (&hx)[8]) {
    constexpr int IP = I >> 2, SG = I & 3;
    a[I][0] = lds32_o<-1024 * IP>(hx[2 * SG]); a[I][1] = lds32_o<-1024 * IP - 512>(hx[2 * SG]);
    a[I][2] = lds32_o<-1024 * IP>(hx[2 * SG + 1]); a[I][3] = lds32_o<-1024 * IP - 512>(hx[2 * SG + 1]);
    if constexpr (I < 15) conv_load_a<I + 1>(a, hx);
}
template <int I> __device__ __forceinline__ void conv_issue(float (&acc)[128], const uint32_t (&a)[16][4], uint64_t db) {
    wgmma_rs<256 - 64 * (I >> 2)>(acc, a[I], db + 64 * (I >> 2) + 2 * (I & 3), I != 0);
    if constexpr (I < 15) conv_issue<I + 1>(acc, a, db);
}
__device__ __forceinline__ void conv_frag_addr(uint32_t (&hx)[8], uint32_t copy_base, int w0, uint32_t xb) {
#pragma unroll
    for (int i = 0; i < 8; i++) { const uint32_t W = (uint32_t)(w0 - 4 * i); hx[i] = copy_base + ((W ^ (((W >> 5) & 3u) << 2) ^ xb) << 2); }
}

__device__ __forceinline__ void kv_cta(const Params& p, uint32_t sb, int j) {
    constexpr uint32_t IN_BYTES = 17408 + 16384, OFF_V = 17408;
    constexpr uint32_t OFF_OUT = 4 * IN_BYTES, OFF_TAPS = OFF_OUT + 4 * 16384;
    constexpr uint32_t B_INF = 0, B_INE = 32, B_OUTF = 64, B_OUTE = 96;
    const uint32_t bars = sb + OFF_BAR;
    const int tid = threadIdx.x, lane = tid & 31;
    if (tid == 0) {
        for (int s = 0; s < 4; s++) { mbar_init(bars + B_INF + 8 * s, 1); mbar_init(bars + B_INE + 8 * s, 8); mbar_init(bars + B_OUTF + 8 * s, 8); mbar_init(bars + B_OUTE + 8 * s, 1); }
        asm volatile("fence.mbarrier_init.release.cluster;" ::: "memory");
    }
    for (int i = tid; i < 512; i += 384) { const uint4 t = __ldg(reinterpret_cast<const uint4*>(p.shift_k) + i); sts128(sb + OFF_TAPS + i * 16, t.x, t.y, t.z, t.w); }
    __syncthreads();
    if (tid == 0) {
        const uint64_t pol = policy_evict_first();
#pragma unroll 1
        for (int i = 0; i < 64 + 3; i++) {
            if (i < 64) {
                const int bf = i & 3, t0 = j * 512 + (i >> 3) * 64, c0 = (i & 7) * 128;
                if (i >= 4) mbar_wait(bars + B_INE + 8 * bf, ((i >> 2) - 1) & 1);
                mbar_expect_tx(bars + B_INF + 8 * bf, 67 * 256 + 64 * 256);
                tma_2d_h(sb + bf * IN_BYTES, &p.tmK, c0, t0 - 3, bars + B_INF + 8 * bf, pol);
                tma_2d_h(sb + bf * IN_BYTES + OFF_V, &p.tmV, c0, t0, bars + B_INF + 8 * bf, pol);
            }
            if (i >= 3) {
                const int o = i - 3, bf = o & 3;
                mbar_wait(bars + B_OUTF + 8 * bf, (o >> 2) & 1);
                if ((o & 7) == 0) H3_GSTAMP(o >> 3);
                tma_store_2d(&p.tmKvT, sb + OFF_OUT + bf * 16384, 1984 - (j * 512 + (o >> 3) * 64), (o & 7) * 128);
                bulk_commit();
                asm volatile("cp.async.bulk.wait_group.read 1;" ::: "memory");
                if (o > 0) mbar_arrive(bars + B_OUTE + 8 * ((o - 1) & 3));
            }
        }
        bulk_wait_all();
        flag_add_after_bulk(p.flags + FL_KV * FLAG_STRIDE);
        H3_GSTAMP(31);
    } else if (tid >= 32) {
#pragma unroll 1
        for (int u = (tid >> 5) - 1; u < 512; u += 11) {
            const int i = u >> 3, bf = i & 3, o = u & 7;
            mbar_wait(bars + B_INF + 8 * bf, (i >> 2) & 1);
            if (i >= 4) mbar_wait(bars + B_OUTE + 8 * bf, ((i >> 2) - 1) & 1);
            const uint32_t out = sb + OFF_OUT + bf * 16384;
            const uint32_t odd = (lane >> 2) & 1, sel0 = odd ? 0x7632u : 0x5410u, sel1 = odd ? 0x5410u : 0x7632u;
            uint32_t kk[2][11], vv[2][8];
            uint4 sw[2];
#pragma unroll
            for (int it = 0; it < 2; it++) {
                const uint32_t rd = sb + bf * IN_BYTES + o * 8 * 256 + (it * 32 + lane) * 4;
#pragma unroll
                for (int r = 0; r < 11; r++) kk[it][r] = lds32(rd + r * 256);
#pragma unroll
                for (int r = 0; r < 8; r++) vv[it][r] = lds32(rd + OFF_V + r * 256);
                sw[it] = lds128(sb + OFF_TAPS + ((i & 7) * 64 + it * 32 + lane) * 16);
            }
#pragma unroll
            for (int it = 0; it < 2; it++) {
                const uint32_t w0 = __byte_perm(sw[it].x, sw[it].z, 0x5410), w1 = __byte_perm(sw[it].x, sw[it].z, 0x7632);
                const uint32_t w2 = __byte_perm(sw[it].y, sw[it].w, 0x5410), w3 = __byte_perm(sw[it].y, sw[it].w, 0x7632);
#pragma unroll
                for (int r = 0; r < 8; r++)
                    vv[it][r] = bf2_mul(bf2_add(bf2_add(bf2_add(bf2_mul(kk[it][r], w3), bf2_mul(kk[it][r + 1], w2)), bf2_mul(kk[it][r + 2], w1)), bf2_mul(kk[it][r + 3], w0)), vv[it][r]);
                const uint32_t r0 = 2 * (it * 32 + lane) + odd, r1 = r0 ^ 1;
                const uint32_t* v = vv[it];
                sts128(out + r0 * 128 + (((7 - o) ^ (r0 & 7)) << 4), __byte_perm(v[0], v[1], sel0), __byte_perm(v[2], v[3], sel0), __byte_perm(v[4], v[5], sel0), __byte_perm(v[6], v[7], sel0));
                sts128(out + r1 * 128 + (((7 - o) ^ (r1 & 7)) << 4), __byte_perm(v[0], v[1], sel1), __byte_perm(v[2], v[3], sel1), __byte_perm(v[4], v[5], sel1), __byte_perm(v[6], v[7], sel1));
            }
            fence_async_smem();
            __syncwarp();
            if (lane == 0) { mbar_arrive(bars + B_INE + 8 * bf); mbar_arrive(bars + B_OUTF + 8 * bf); }
        }
    }
}

__global__ void __launch_bounds__(384, 1) h3_kernel(const __grid_constant__ Params p) {
    extern __shared__ uint8_t smem_raw[];
    const uint32_t sb = (smem_u32(smem_raw) + 1023) & ~1023u;
    const uint32_t bars = sb + OFF_BAR;
    const int tid = threadIdx.x;
    const int wg = __shfl_sync(0xffffffffu, tid >> 7, 0);
    const int lane = tid & 31;
    const int cta = blockIdx.x;
    const int pair = cta >> 1;
    const uint32_t rank = cta & 1;

    if (cta >= NCTA) { kv_cta(p, sb, cta - NCTA); return; }

    uint32_t x[32];
    if (wg != 0) {
        const uint4* src = reinterpret_cast<const uint4*>(p.q + (size_t)(cta * 16 + ((tid >> 5) - 4) * 2 + (lane >> 4)) * D) + (lane & 15);
#pragma unroll
        for (int i = 0; i < 8; i++) { const uint4 t = __ldg(src + i * 16); x[4 * i] = t.x; x[4 * i + 1] = t.y; x[4 * i + 2] = t.z; x[4 * i + 3] = t.w; }
    }
    if (tid == 0) {
        H3_STAMP(0);
#pragma unroll 1
        for (int s = 0; s < 4; s++) { mbar_init(bars + BAR_FULLA + 8 * s, 1); mbar_init(bars + BAR_EMPTYA + 8 * s, 4); }
#pragma unroll 1
        for (int s = 0; s < 6; s++) { mbar_init(bars + BAR_FULLB + 8 * s, 1); mbar_init(bars + BAR_EMPTYB + 8 * s, 4); }
        mbar_init(bars + BAR_STGFULL, 8);
        mbar_init(bars + BAR_STGEMPTY, 1);
        mbar_init(bars + BAR_ALTFULL, 8);
        mbar_init(bars + BAR_ALT2FULL, 8);
        mbar_init(bars + BAR_OPFULL, 1);
        asm volatile("fence.mbarrier_init.release.cluster;" ::: "memory");
    }
    __syncthreads();
    cluster_arrive();

    const int grp = (pair < 4) ? 0 : (pair < 36) ? ((pair - 4) & 7) : 1 + (pair - 36) % 7;
    const int gj = (pair < 4) ? 4 + pair : (pair < 36) ? ((pair - 4) >> 3) : 4 + (pair - 36) / 7;
    const int m1 = 2 * grp + (int)rank, nb1 = gj;
    const int m2 = ((grp >> 2) << 3) | gj, pn = grp & 3;
    const int nh = 24 + pn;
    const int n2 = pn * 256 + (int)rank * 128;

    if (wg == 0) {
        asm volatile("setmaxnreg.dec.sync.aligned.u32 40;\n");
        const int warp = tid >> 5;
        if (warp == 0) {
            if (lane == 0) {
                const uint64_t pol = policy_evict_first();
                const int mrow1 = m1 * 128, mrow2 = m2 * 128 + (int)rank * 64, ngh = nh * 2 + (int)rank;
                const CUtensorMap* tmW = rank ? &p.tmWu2 : &p.tmWg2;
                const uint32_t woff = 16384 + rank * 16384;
                cluster_wait();
#pragma unroll 1
                for (int j = 0; j < 4; j++) {
                    const uint32_t full = bars + BAR_FULLA + 8 * j;
                    mbar_expect_tx(full, A_STAGE);
                    tma_3d_mc_h(sb + j * A_STAGE + woff, tmW, 0, j * 64, nb1 * 2, full, pol);
                }
                flag_wait(p.flags + (FL_XN + m1) * FLAG_STRIDE, 64);
                H3_STAMP(1);
#pragma unroll 1
                for (int j = 0; j < 4; j++) tma_2d(sb + j * A_STAGE, &p.tmXn128, j * 64, mrow1, bars + BAR_FULLA + 8 * j);
#pragma unroll 1
                for (int g = 4; g < 48; g++) {
                    const int st = g & 3, k0 = (g & 15) * 64, ng = ((g >> 4) * 8 + nb1) * 2;
                    const uint32_t full = bars + BAR_FULLA + 8 * st, a = sb + st * A_STAGE;
                    mbar_wait(bars + BAR_EMPTYA + 8 * st, ((g >> 2) - 1) & 1);
                    H3_TR(1, 256 + g);
                    mbar_expect_tx(full, A_STAGE);
                    tma_2d(a, &p.tmXn128, k0, mrow1, full);
                    tma_3d_mc_h(a + woff, tmW, 0, k0, ng, full, pol);
                    if (g == 3 * ((cta & 31) >> 2) - 2) { pf_bulk_h(p.k + (size_t)cta * 16 * D, 32768, pol); pf_bulk_h(p.v + (size_t)cta * 16 * D, 32768, pol); }
                }
                flag_wait(p.flags + (FL_XN + m2) * FLAG_STRIDE, 64);
                pf_bulk_h(p.ssm_k + (size_t)cta * 8 * S, 32768, pol);
                int st = 0; uint32_t ph = 1;
#pragma unroll 1
                for (int e = 0; e < 16; e++) {
                    const uint32_t full = bars + BAR_FULLB + 8 * st, a = sb + st * B_STAGE;
                    if (e < 6) {
                        if (e != 2 && e != 5) mbar_wait(bars + BAR_EMPTYA + 8 * (e - (e >= 3)), 1);
                    } else {
                        mbar_wait(bars + BAR_EMPTYB + 8 * st, ph);
                    }
                    H3_TR(1, 304 + e);
                    mbar_expect_tx(full, B_STAGE);
                                        tma_2d_mc(a + rank * 8192, &p.tmXn64, e * 64, mrow2, full);
                    tma_3d_h(a + 16384, &p.tmWg1, 0, e * 64, ngh, full, pol);
                    tma_3d_h(a + 24576, &p.tmWu1, 0, e * 64, ngh, full, pol);
                    if (++st == 6) { st = 0; ph ^= 1; }
                }
                mbar_wait(bars + BAR_EMPTYB + 8 * ST_H, 1);
                mbar_expect_tx(bars + BAR_FULLB + 8 * ST_H, 32768);
                bulk_g2s_h(sb + ST_H * B_STAGE, p.ssm_k + (size_t)cta * 8 * S, 32768, bars + BAR_FULLB + 8 * ST_H, pol);
                unsigned kv_ready;
                asm volatile("ld.acquire.gpu.global.u32 %0, [%1];" : "=r"(kv_ready) : "l"(p.flags + FL_KV * FLAG_STRIDE) : "memory");
#pragma unroll 1
                for (int pass = 0; pass < 2; pass++) {
                    if ((pass == 0) == (kv_ready >= 4)) {
                        mbar_wait(bars + BAR_EMPTYB + 8 * ST_U, 1);
                        flag_wait(p.flags + FL_KV * FLAG_STRIDE, 4);
                        mbar_expect_tx(bars + BAR_FULLB + 8 * ST_U, 32768);
#pragma unroll 1
                        for (int ch = 0; ch < 8; ch++) bulk_g2s_h(sb + ST_U * B_STAGE + ch * U_PITCH, p.kvT + (size_t)(cta * 8 + ch) * S, 4096, bars + BAR_FULLB + 8 * ST_U, pol);
                    }
                    if (pass == 0) {
#pragma unroll 1
                        for (int c = 0; c < 4; c++) { mbar_wait(bars + BAR_EMPTYB + 8 * c, 0); mbar_arrive(bars + BAR_FULLB + 8 * c); }
                    }
                }
                flag_wait(p.flags + (FL_H + m2) * FLAG_STRIDE, 16);
                H3_STAMP(2);
                int i6 = 0; uint32_t rho = 0;
#pragma unroll 1
                for (int kb = 0; kb < 56; kb++) {
                    const int sg = (0x512034 >> (4 * i6)) & 15;
                    const uint32_t par = ((0x21u >> i6) & 1u) ^ rho;
                    const uint32_t full = bars + BAR_FULLB + 8 * sg, a = sb + sg * B_STAGE;
                    mbar_wait(bars + BAR_EMPTYB + 8 * sg, par ^ 1);
                    if (kb == 32) flag_wait(p.flags + (FL_H2 + m2) * FLAG_STRIDE, 16);
                    H3_TR(2, 256 + kb);
                    mbar_expect_tx(full, B_STAGE);
                    tma_2d_mc(a + rank * 8192, &p.tmH64, kb * 64, mrow2, full);
                    tma_3d(a + 16384, &p.tmWd, 0, kb * 64, n2 >> 6, full);
                    if (++i6 == 6) { i6 = 0; rho ^= 1; }
                }
                mbar_wait(bars + BAR_EMPTYB + 0, 0);
                mbar_expect_tx(bars + BAR_FULLB + 0, 32768);
                tma_2d(sb, &p.tmX128, n2, m2 * 128, bars + BAR_FULLB + 0);
                tma_2d(sb + 16384, &p.tmX128, n2 + 64, m2 * 128, bars + BAR_FULLB + 0);
                mbar_wait(bars + BAR_OPFULL, 0);
                unsigned old;
                asm volatile("atom.acq_rel.gpu.global.add.u32 %0, [%1], 1;" : "=r"(old) : "l"(p.flags + FL_DONE * FLAG_STRIDE) : "memory");
                if (old == NCTA - 1) {
#pragma unroll 1
                    for (int i = 0; i < FL_COUNT; i++) p.flags[i * FLAG_STRIDE] = 0;
                }
            } else {
                cluster_wait();
            }
        } else {
            if (tid == 32) H3_GSTAMP(30);
            cluster_wait();
            const int wt = tid - 32;
#pragma unroll 1
            for (int Ri = 0; Ri < 7; Ri++) {
                const int R = (Ri == 5) ? 6 : (Ri == 6) ? 5 : Ri;
                const uint32_t buf = (R == 4) ? sb + ST_ALT2 * B_STAGE : (R == 6) ? sb + ST_ALT * B_STAGE : sb + OFF_STG;
                mbar_wait_idle(bars + ((R == 4) ? BAR_ALT2FULL : (R == 6) ? BAR_ALTFULL : BAR_STGFULL), (R < 4) ? (R & 1) : 0);
                if (wt == 0) H3_TR(3, 200 + R * 4);
#pragma unroll 1
                for (int i0 = wt; i0 < 1024; i0 += 2 * 96) {
                    const int i1 = i0 + 96;
                    const uint32_t a0 = buf + (i0 >> 9) * 16384 + (i0 & 511) * 16;
                    const uint32_t a1 = (i1 < 1024) ? buf + (i1 >> 9) * 16384 + (i1 & 511) * 16 : a0;
                    uint4 g0 = lds128(a0), u0 = lds128(a0 + 8192), g1 = lds128(a1), u1 = lds128(a1 + 8192);
                    g0.x = bf2_mul(silu_bf2(g0.x), u0.x); g0.y = bf2_mul(silu_bf2(g0.y), u0.y); g0.z = bf2_mul(silu_bf2(g0.z), u0.z); g0.w = bf2_mul(silu_bf2(g0.w), u0.w);
                    g1.x = bf2_mul(silu_bf2(g1.x), u1.x); g1.y = bf2_mul(silu_bf2(g1.y), u1.y); g1.z = bf2_mul(silu_bf2(g1.z), u1.z); g1.w = bf2_mul(silu_bf2(g1.w), u1.w);
                    sts128(a0, g0.x, g0.y, g0.z, g0.w);
                    if (i1 < 1024) sts128(a1, g1.x, g1.y, g1.z, g1.w);
                }
                if (wt == 0) H3_TR(3, 200 + R * 4 + 1);
                fence_async_smem();
                bar_sync(4, 96);
                if (wt == 0) {
                    const int mm = (R < 6) ? m1 : m2;
                    const int col = (R < 6) ? (8 * (R >> 1) + nb1) * 128 + (R & 1) * 64 : nh * 128 + (int)rank * 64;
                    tma_store_2d(&p.tmH64, buf, col, mm * 128);
                    tma_store_2d(&p.tmH64, buf + 16384, col, mm * 128 + 64);
                    bulk_commit();
                    bulk_wait_read();
                    if (R != 4 && R != 6) mbar_arrive(bars + BAR_STGEMPTY);
                    else {
                        const uint32_t eb = bars + BAR_EMPTYB + 8 * ((R == 4) ? ST_ALT2 : ST_ALT);
                        mbar_arrive_cta(eb, 0); mbar_arrive_cta(eb, 0); mbar_arrive_cta(eb, 1); mbar_arrive_cta(eb, 1);
                    }
                    H3_TR(3, 200 + R * 4 + 2);
                    if (R == 1 || R == 3 || R >= 5) {
                        bulk_wait_all();
                        flag_add_after_bulk(p.flags + ((R < 4 ? FL_H : FL_H2) + mm) * FLAG_STRIDE);
                    }
                }
            }
            if (wt == 0) {
                mbar_wait(bars + BAR_FULLB + 8 * 3, 0); mbar_wait(bars + BAR_FULLB + 8 * 3, 1); mbar_wait(bars + BAR_FULLB + 8 * 3, 0);
                pf_2d(&p.tmX128, n2, m2 * 128); pf_2d(&p.tmX128, n2 + 64, m2 * 128);
                flag_wait(p.flags + (FL_Y + (n2 >> 7)) * FLAG_STRIDE, 128);
                mbar_expect_tx(bars + BAR_OPFULL, 32768);
                tma_2d(sb + OFF_STG, &p.tmY2T, 1984 - m2 * 128, n2, bars + BAR_OPFULL);
                tma_2d(sb + OFF_STG + 16384, &p.tmY2T, 1920 - m2 * 128, n2, bars + BAR_OPFULL);
            }
        }
        __syncwarp();
        cluster_sync();
    } else {
        asm volatile("setmaxnreg.inc.sync.aligned.u32 232;\n");
        const int cw = wg - 1;
        const int w = (tid >> 5) & 3;
        const int wtid = tid & 127;

        {
            const int rl = (cw * 4 + w) * 2 + (lane >> 4);
            const uint32_t src = sb + OFF_STG + rl * 2048 + (lane & 15) * 16;
            if (tid == 128) H3_STAMP(15);
            float s0 = 0.f, s1 = 0.f, s2 = 0.f, s3 = 0.f;
#pragma unroll
            for (int i = 0; i < 32; i += 2) { s0 += bf_lo(x[i]); s1 += bf_hi(x[i]); s2 += bf_lo(x[i + 1]); s3 += bf_hi(x[i + 1]); }
            float s = (s0 + s1) + (s2 + s3);
#pragma unroll
            for (int o = 8; o > 0; o >>= 1) s += __shfl_xor_sync(0xffffffffu, s, o);
            const float mu = s * (1.0f / D);
            s0 = s1 = s2 = s3 = 0.f;
#pragma unroll
            for (int i = 0; i < 32; i += 2) {
                const float a = bf_lo(x[i]) - mu, b = bf_hi(x[i]) - mu, c = bf_lo(x[i + 1]) - mu, d = bf_hi(x[i + 1]) - mu;
                s0 = fmaf(a, a, s0); s1 = fmaf(b, b, s1); s2 = fmaf(c, c, s2); s3 = fmaf(d, d, s3);
            }
            float v = (s0 + s1) + (s2 + s3);
#pragma unroll
            for (int o = 8; o > 0; o >>= 1) v += __shfl_xor_sync(0xffffffffu, v, o);
            if (tid == 128) H3_STAMP(17);
            const uint32_t mu2 = pack_bf2(mu, mu);
            const float vb = bf_lo(pack_bf2(v * (1.0f / D), 0.f));
            const float ve = bf_lo(pack_bf2(vb + 1e-5f, 0.f));
            const float sd = bf_lo(pack_bf2(sqrtf(ve), 0.f));
            const float inv = __frcp_rn(sd);
#pragma unroll
            for (int i = 0; i < 8; i++) {
                uint32_t oo[4];
#pragma unroll
                for (int e = 0; e < 4; e++) { const uint32_t dd = bf2_sub(x[4 * i + e], mu2); oo[e] = pack_bf2(bf_lo(dd) * inv, bf_hi(dd) * inv); }
                sts128(src + i * 256, oo[0], oo[1], oo[2], oo[3]);
            }
            if ((lane & 15) == 0) asm volatile("st.shared.v2.b32 [%0], {%1, %2};" :: "r"(bars + OFF_STAT + rl * 8), "r"(mu2), "r"(__float_as_uint(inv)) : "memory");
            fence_async_smem();
            __syncwarp();
            if (tid == 128) H3_STAMP(18);
            if (lane == 0) {
                bulk_s2g(p.xn + (size_t)(cta * 16 + (cw * 4 + w) * 2) * D, sb + OFF_STG + (cw * 4 + w) * 4096, 4096);
                bulk_s2g(p.stats + cta * 16 + (cw * 4 + w) * 2, bars + OFF_STAT + (cw * 4 + w) * 16, 16);
                bulk_commit();
                bulk_wait_all();
                flag_add_after_bulk(p.flags + (FL_XN + (cta >> 3)) * FLAG_STRIDE);
            }
            if (tid == 128) H3_STAMP(19);
            bar_sync(3, 256);
        }
        if (tid == 128) H3_STAMP(3);
        cluster_wait();

        const uint32_t lrow = w * 16 + (lane & 7) + ((lane >> 3) & 1) * 8;
        const uint32_t lrow7 = lane & 7;
        const uint32_t lgrp = lane >> 4;
        const uint32_t stg_lane = sb + OFF_STG + cw * 16384 + lrow * 128;
        const uint64_t descA = make_desc(sb + cw * 8192, 16, 1024);
        const uint64_t descB = make_desc(sb + 16384, 8192, 1024);

        int st = 0; uint32_t ph = 0;
        uint32_t pg[32], pu[32], qg[16], qu[16];
        {
            float acc[128];
            int prev = 0;
#pragma unroll 1
            for (int g = 0; g < 64; g++) {
                const int kb = g & 15;
                if (g < 48) {
                    const int sa = g & 3;
                    mbar_wait(bars + BAR_FULLA + 8 * sa, (g >> 2) & 1);
                    if (g == 0 && tid == 128) H3_STAMP(4);
                    if (wtid == 0) H3_TR(1, cw * 128 + g * 2);
                    const uint64_t da = descA + sa * (A_STAGE >> 4), db = descB + sa * (A_STAGE >> 4);
                    wg_fence();
                    wgmma_256(acc, da, db, kb != 0);
#pragma unroll
                    for (int k = 1; k < 4; k++) wgmma_256(acc, da + k * 2, db + k * 128, 1);
                    wg_commit();
                } else {
                    mbar_wait(bars + BAR_FULLB + 8 * st, ph);
                    if (wtid == 0) H3_TR(1, cw * 128 + g * 2);
                    const uint64_t da = descA + st * (B_STAGE >> 4), db = descB + st * (B_STAGE >> 4);
                    wg_fence();
                    wgmma_128_lo(acc, da, db, kb != 0);
#pragma unroll
                    for (int k = 1; k < 4; k++) wgmma_128_lo(acc, da + k * 2, db + k * 128, 1);
                    wg_commit();
                }
                wg_wait<1>();
                if (wtid == 0) H3_TR(1, cw * 128 + g * 2 + 1);
                if (kb > 0) {
                    if (wtid < 2) mbar_arrive_cta(bars + ((g > 48) ? BAR_EMPTYB + 8 * prev : BAR_EMPTYA + 8 * ((g - 1) & 3)), wtid);
                }
                if (g >= 48) { prev = st; if (++st == 6) { st = 0; ph ^= 1; } }
                if (g >= 16 && g < 48) {
                    const int pc = (kb < 4) ? kb : ((kb >= 9 && kb < 13) ? kb - 5 : -1);
                    if (pc >= 0) {
                        if (pc == 0 && g >= 32) mbar_wait(bars + BAR_STGEMPTY, 1);
                        if (pc == 4) mbar_wait(bars + BAR_STGEMPTY, 0);
                        stage_piece_dyn(pc, pg, pu, stg_lane, lrow7, lgrp);
                        if ((pc & 3) == 3) { __syncwarp(); if (lane == 0) mbar_arrive(bars + BAR_STGFULL); }
                    }
                }
                if (kb == 15 && g < 48) {
                    wg_wait<0>();
                    if (wtid == 0) H3_TR(1, 330 + cw * 16 + (g >> 4) * 2);
                    if (wtid < 2) mbar_arrive_cta(bars + BAR_EMPTYA + 24, wtid);
#pragma unroll
                    for (int i = 0; i < 32; i++) { pg[i] = pack_bf2(acc[2 * i], acc[2 * i + 1]); pu[i] = pack_bf2(acc[64 + 2 * i], acc[64 + 2 * i + 1]); }
                    if (wtid == 0) H3_TR(1, 330 + cw * 16 + (g >> 4) * 2 + 1);
                    if (tid == 128) H3_STAMP(5 + (g >> 4));
                }
            }
            wg_wait<0>();
            if (wtid < 2) mbar_arrive_cta(bars + BAR_EMPTYB + 8 * prev, wtid);
#pragma unroll
            for (int i = 0; i < 16; i++) { qg[i] = pack_bf2(acc[2 * i], acc[2 * i + 1]); qu[i] = pack_bf2(acc[32 + 2 * i], acc[32 + 2 * i + 1]); }
            if (tid == 128) H3_STAMP(14);
        }
        mbar_wait(bars + BAR_FULLB + 8 * ST_ALT2, 1);
        {
            const uint32_t alt_lane = sb + ST_ALT2 * B_STAGE + cw * 16384 + lrow * 128;
            stage_piece<0>(pg, pu, alt_lane, lrow7, lgrp); stage_piece<1>(pg, pu, alt_lane, lrow7, lgrp);
            stage_piece<2>(pg, pu, alt_lane, lrow7, lgrp); stage_piece<3>(pg, pu, alt_lane, lrow7, lgrp);
            __syncwarp(); if (lane == 0) mbar_arrive(bars + BAR_ALT2FULL);
        }
        mbar_wait(bars + BAR_STGEMPTY, 1);
        stage_piece<4>(pg, pu, stg_lane, lrow7, lgrp); stage_piece<5>(pg, pu, stg_lane, lrow7, lgrp);
        stage_piece<6>(pg, pu, stg_lane, lrow7, lgrp); stage_piece<7>(pg, pu, stg_lane, lrow7, lgrp);
        __syncwarp(); if (lane == 0) mbar_arrive(bars + BAR_STGFULL);
        mbar_wait(bars + BAR_FULLB + 8 * ST_ALT, 1);
        {
            const uint32_t alt_lane = sb + ST_ALT * B_STAGE + cw * 16384 + lrow * 128;
#pragma unroll
            for (int i = 0; i < 4; i++) {
                const uint32_t addr = alt_lane + (((2 * i + lgrp) ^ lrow7) << 4);
                stsm_x4(addr, qg[4 * i], qg[4 * i + 1], qg[4 * i + 2], qg[4 * i + 3]);
                stsm_x4(addr + 8192, qu[4 * i], qu[4 * i + 1], qu[4 * i + 2], qu[4 * i + 3]);
            }
            __syncwarp(); if (lane == 0) mbar_arrive(bars + BAR_ALTFULL);
        }
        if (tid == 128) H3_STAMP(8);
        {
            const int r = lane >> 2, c4 = lane & 3;
            if (lane == 0) H3_TR(3, (cw * 4 + w) * 16 + 0);
            mbar_wait(bars + BAR_FULLB + 8 * ST_H, 0);
            mbar_wait(bars + BAR_FULLB + 8 * ST_C0, 1);
            mbar_wait(bars + BAR_FULLB + 8 * ST_C1, 1);
            if (tid == 128) H3_STAMP(23);
            {
                const uint32_t sH = sb + ST_H * B_STAGE + (cw * 4 + w) * 4096;
                const uint32_t sA = sb + (w >> 1) * B_STAGE + ((w & 1) * 2 + cw) * 8192, sB = sA + 4096;
                uint4 hv[8]; uint32_t hp[8];
#pragma unroll
                for (int i = 0; i < 8; i++) {
                    const int Q = i * 32 + lane;
                    hv[i] = lds128(sH + (255 - Q) * 16);
                    hp[i] = lds32(sH + (254 - Q) * 16 + 12);
                }
                if (lane == 31) hp[7] = 0;
                const uint32_t qs = (uint32_t)(lane ^ ((lane >> 3) & 3)) * 16;
#pragma unroll
                for (int i = 0; i < 8; i++) {
                    const uint4 a = hv[i];
                    const uint32_t prev = hp[i];
                    sts128(sA + i * 512 + qs, __byte_perm(a.w, 0, 0x1032), __byte_perm(a.z, 0, 0x1032), __byte_perm(a.y, 0, 0x1032), __byte_perm(a.x, 0, 0x1032));
                    sts128(sB + i * 512 + (qs ^ 64), __byte_perm(a.w, a.z, 0x7610), __byte_perm(a.z, a.y, 0x7610), __byte_perm(a.y, a.x, 0x7610), __byte_perm(a.x, prev, 0x7610));
                }
            }
            if (tid == 128) H3_STAMP(24);
            mbar_wait(bars + BAR_FULLB + 8 * ST_U, 0);
            if (tid == 128) H3_STAMP(25);
            if (lane < 8) sts128(sb + ST_U * B_STAGE + (cw * 4 + w) * U_PITCH + 4096 + lane * 16, 0, 0, 0, 0);
            fence_async_smem();
            bar_sync(1 + cw, 128);
            if (wtid < 2) mbar_arrive_cta(bars + BAR_EMPTYB + 8 * ST_H, wtid);
            if (cw == 1) bar_arrive(5, 256);
            if (tid == 128) H3_STAMP(9);
            const uint32_t podd = r & 1, b0 = (r >> 1) & 1, b1 = r >> 2;
            const int w0 = 1023 - w + c4 - 32 * (r >> 1);
            const uint32_t cpy = podd ? 0u : 4096u, xb = podd ? 0u : 16u;
            const int y0 = 2 * w + (int)podd - 2 * c4;
            const uint32_t mask0 = (r >> 1) ? 0xFFFFFFFFu : ((y0 >= 0 ? 0x0000FFFFu : 0u) | (y0 >= 1 ? 0xFFFF0000u : 0u));
            uint32_t a[16][4];
            {
                uint32_t hx[8];
                conv_frag_addr(hx, sb + cw * 8192 + cpy, w0, xb);
                conv_load_a<0>(a, hx);
                a[0][0] &= mask0;
            }
            const uint2 dq = __ldg(reinterpret_cast<const uint2*>(p.ssm_D + cta * 8 + cw * 4));
            auto conv_finish = [&](int cp) {
                const uint32_t sA = sb + (cp >> 1) * B_STAGE + ((cp & 1) * 2 + cw) * 8192;
                const uint32_t sU = sb + ST_U * B_STAGE + (cw * 4 + cp) * U_PITCH;
                const uint32_t dw = (cp & 2) ? dq.y : dq.x;
                const uint32_t d2 = __byte_perm(dw, 0, (cp & 1) ? 0x3232 : 0x1010);
#pragma unroll
                for (int i = 0; i < 2; i++) {
                    const uint32_t beta = 64 * w + 32 * i + lane;
                    const uint4 kv = lds128(sU + beta * 16);
                    const uint32_t y0w = lds32_o<0>(sA + beta * 4), y1w = lds32_o<1024>(sA + beta * 4), y2w = lds32_o<2048>(sA + beta * 4), y3w = lds32_o<3072>(sA + beta * 4);
                    sts128(sU + beta * 16, bf2_add(y0w, bf2_mul(kv.x, d2)), bf2_add(y1w, bf2_mul(kv.y, d2)), bf2_add(y2w, bf2_mul(kv.z, d2)), bf2_add(y3w, bf2_mul(kv.w, d2)));
                }
            };
            auto conv_store = [&](int cp) {
                const int ch = cw * 4 + cp;
                fence_async_smem();
                __syncwarp();
                if (lane == 0) { bulk_s2g(p.y2T + (size_t)(cta * 8 + ch) * S + w * 512, sb + ST_U * B_STAGE + ch * U_PITCH + w * 1024, 1024); bulk_commit(); }
                if (cp & 1) { bar_sync(1 + cw, 128); if (wtid < 2) mbar_arrive_cta(bars + BAR_EMPTYB + 8 * (cp >> 1), wtid); }
                if (lane == 0) H3_TR(3, (cw * 4 + w) * 16 + 3 + cp * 3);
            };
#pragma unroll 1
            for (int ci = 0; ci < 4; ci++) {
                const int k = 2 * ci + cw;
                float acc[128];
                if (lane == 0) H3_TR(3, (cw * 4 + w) * 16 + 1 + ci * 3);
                bar_sync(5 + cw, 256);
                wg_fence();
                conv_issue<0>(acc, a, make_desc_noswz(sb + ST_U * B_STAGE + (cw * 4 + ci) * U_PITCH, 16, 128));
                wg_commit();
                if (k < 7) bar_arrive(5 + (cw ^ 1), 256);
                if (ci > 0) conv_finish(ci - 1);
                wg_wait<0>();
                if (lane == 0) H3_TR(3, (cw * 4 + w) * 16 + 2 + ci * 3);
                if (ci > 0) conv_store(ci - 1);
                float f[16];
                {
                    float wv[34];
#pragma unroll
                    for (int i = 0; i < 16; i++) {
#pragma unroll
                        for (int jj = 0; jj < 2; jj++) {
                            const float ve = acc[8 * i + jj] + ((2 * i + 4 < 32) ? acc[4 * (2 * i + 4) + 2 + jj] : 0.f);
                            const float vo = acc[8 * i + 4 + jj] + ((2 * i + 5 < 32) ? acc[4 * (2 * i + 5) + 2 + jj] : 0.f);
                            const float vn = (i < 15) ? acc[8 * i + 8 + jj] + ((2 * i + 6 < 32) ? acc[4 * (2 * i + 6) + 2 + jj] : 0.f) : 0.f;
                            wv[2 * i + jj] = (b0 ? vn : ve) + __shfl_xor_sync(0xffffffffu, vo, 8);
                        }
                    }
                    wv[32] = wv[33] = 0.f;
#pragma unroll
                    for (int kk = 0; kk < 8; kk++)
#pragma unroll
                        for (int jj = 0; jj < 2; jj++)
                            f[2 * kk + jj] = (b1 ? wv[4 * kk + 4 + jj] : wv[4 * kk + jj]) + __shfl_xor_sync(0xffffffffu, wv[4 * kk + 2 + jj], 16);
                }
                {
                    const uint32_t sA = sb + (ci >> 1) * B_STAGE + ((ci & 1) * 2 + cw) * 8192;
#pragma unroll
                    for (int kk = 0; kk < 8; kk++) {
                        const float keep = podd ? f[2 * kk + 1] : f[2 * kk];
                        const float recv = __shfl_xor_sync(0xffffffffu, podd ? f[2 * kk] : f[2 * kk + 1], 4);
                        const uint32_t yw = pack_bf2(podd ? recv : keep, podd ? keep : recv);
                        asm volatile("st.shared.b32 [%0], %1;" :: "r"(sA + w * 1024 + (32 * kk + 8 * (r >> 1) + 2 * c4 + podd) * 4), "r"(yw) : "memory");
                    }
                }
                if (lane == 0 && ci == 1) H3_TR(3, (cw * 4 + w) * 16 + 13);
                if (ci < 3) {
                    uint32_t hx[8];
                    conv_frag_addr(hx, sb + ((ci + 1) >> 1) * B_STAGE + (((ci + 1) & 1) * 2 + cw) * 8192 + cpy, w0, xb);
                    conv_load_a<0>(a, hx);
                    a[0][0] &= mask0;
                }
                if (lane == 0 && ci == 1) H3_TR(3, (cw * 4 + w) * 16 + 14);
            }
            bar_sync(1 + cw, 128);
            conv_finish(3);
            conv_store(3);
            if (lane == 0) bulk_wait_read();
            bar_sync(1 + cw, 128);
            if (wtid < 2) mbar_arrive_cta(bars + BAR_EMPTYB + 8 * ST_U, wtid);
            if (tid == 128) H3_STAMP(11);
        }
        {
            float acc[64];
            const int srow = m2 * 128 + cw * 64 + w * 16 + (lane >> 2);
            const uint2 st0 = __ldcg(p.stats + srow), st1 = __ldcg(p.stats + srow + 8);
            int i6 = 0, prev = 0; uint32_t rho = 0;
#pragma unroll 1
            for (int kb = 0; kb < 56; kb++) {
                const int sg = (0x512034 >> (4 * i6)) & 15;
                mbar_wait(bars + BAR_FULLB + 8 * sg, ((0x21u >> i6) & 1u) ^ rho);
                if (wtid == 0) H3_TR(2, cw * 128 + kb * 2);
                if (tid == 128) { if (kb == 0) H3_STAMP(28); if (kb == 8) H3_STAMP(10); if (kb == 16) H3_STAMP(16); if (kb == 32) H3_STAMP(26); if (kb == 44) H3_STAMP(27); }
                const uint64_t da = descA + sg * (B_STAGE >> 4), db = descB + sg * (B_STAGE >> 4);
                wg_fence();
                wgmma_128(acc, da, db, kb != 0);
#pragma unroll
                for (int k = 1; k < 4; k++) wgmma_128(acc, da + k * 2, db + k * 128, 1);
                wg_commit();
                                if (kb == 8 && lane == 0) { bulk_wait_all(); flag_add_after_bulk(p.flags + (FL_Y + (cta >> 4)) * FLAG_STRIDE); }
                wg_wait<1>();
                if (wtid == 0) H3_TR(2, cw * 128 + kb * 2 + 1);
                if (kb > 0 && wtid < 2) mbar_arrive_cta(bars + BAR_EMPTYB + 8 * prev, wtid);
                prev = sg;
                if (++i6 == 6) { i6 = 0; rho ^= 1; }
            }
            mbar_wait(bars + BAR_OPFULL, 0);
            wg_wait<0>();
            if (tid == 128) H3_STAMP(12);
            mbar_wait(bars + BAR_FULLB + 0, 1);
            if (tid == 128) H3_STAMP(20);
            const float inv0 = __uint_as_float(st0.y), inv1 = __uint_as_float(st1.y);
            const uint32_t ycol = sb + OFF_STG + cw * 16384 + (((7 - 2 * w - ((lane >> 3) & 1)) ^ lrow7) << 4) + lrow7 * 128;
            const uint32_t xrow = sb + (cw * 64 + lrow) * 128;
#pragma unroll 1
            for (int g2 = 0; g2 < 2; g2++) {
#pragma unroll
                for (int hh = 0; hh < 4; hh++) {
                    const uint32_t grp = hh * 2 + lgrp;
                    const uint32_t xa = xrow + g2 * 16384 + ((grp ^ lrow7) << 4);
                    uint32_t x[4], y[4], o[4];
                    ldsm_x4(xa, x[0], x[1], x[2], x[3]);
                    ldsm_x4_t(ycol + (g2 * 8 + grp) * 1024, y[0], y[1], y[2], y[3]);
#pragma unroll
                    for (int i = 0; i < 4; i++) {
                        const uint32_t dd = bf2_sub(x[i], (i & 1) ? st1.x : st0.x);
                        const float iv = (i & 1) ? inv1 : inv0;
                        const uint32_t xn = pack_bf2(bf_lo(dd) * iv, bf_hi(dd) * iv);
                        o[i] = bf2_add(x[i], bf2_mul(bf2_mul(xn, y[i]), silu_bf2(pack_bf2(acc[8 * hh + 2 * i], acc[8 * hh + 2 * i + 1]))));
                    }
                    stsm_x4(xa, o[0], o[1], o[2], o[3]);
                }
#pragma unroll
                for (int i = 0; i < 32; i++) acc[i] = acc[i + 32];
                fence_async_smem();
                bar_sync(1 + cw, 128);
                if (wtid == 0) { tma_store_2d(&p.tmOut64, sb + g2 * 16384 + cw * 8192, n2 + g2 * 64, m2 * 128 + cw * 64); bulk_commit(); }
            }
            if (tid == 128) H3_STAMP(21);
            if (wtid == 0) bulk_wait_read();
            if (tid == 128) { H3_STAMP(13); H3_GSTAMP(31); }
        }
        cluster_sync();
    }
}

typedef CUresult (*EncodeTiledFn)(CUtensorMap*, CUtensorMapDataType, cuuint32_t, void*, const cuuint64_t*, const cuuint64_t*,
                                  const cuuint32_t*, const cuuint32_t*, CUtensorMapInterleave, CUtensorMapSwizzle,
                                  CUtensorMapL2promotion, CUtensorMapFloatOOBfill);

static void make_map(EncodeTiledFn enc, CUtensorMap* m, const void* ptr, int rank, const uint64_t* dims, const uint64_t* strides, const uint32_t* box,
                     CUtensorMapSwizzle swz = CU_TENSOR_MAP_SWIZZLE_128B) {
    cuuint64_t d[3], s[2];
    cuuint32_t b[3], es[3] = {1, 1, 1};
    for (int i = 0; i < rank; i++) { d[i] = dims[i]; b[i] = box[i]; }
    for (int i = 0; i + 1 < rank; i++) s[i] = strides[i];
    CUresult r = enc(m, CU_TENSOR_MAP_DATA_TYPE_BFLOAT16, rank, const_cast<void*>(ptr), d, s, b, es, CU_TENSOR_MAP_INTERLEAVE_NONE,
                     swz, CU_TENSOR_MAP_L2_PROMOTION_L2_128B, CU_TENSOR_MAP_FLOAT_OOB_FILL_NONE);
    if (r != CUDA_SUCCESS) fprintf(stderr, "cuTensorMapEncodeTiled failed: %d\n", (int)r);
}
static void map2d(EncodeTiledFn enc, CUtensorMap* m, const void* ptr, uint64_t cols, uint64_t rows, uint32_t box_rows) {
    const uint64_t d[2] = {cols, rows}, s[1] = {cols * 2};
    const uint32_t b[2] = {64, box_rows};
    make_map(enc, m, ptr, 2, d, s, b);
}
static void map3d(EncodeTiledFn enc, CUtensorMap* m, const void* ptr, uint64_t cols, uint64_t rows, uint32_t groups) {
    const uint64_t d[3] = {64, rows, cols / 64}, s[2] = {cols * 2, 128};
    const uint32_t b[3] = {64, 64, groups};
    make_map(enc, m, ptr, 3, d, s, b);
}

static long long* g_dbg_ptr = nullptr;

}

extern "C" void kernel_launch(void* const* d_in, const int* in_sizes, int n_in, void* d_out, int out_size) {
    using namespace h3;
    (void)in_sizes; (void)n_in; (void)out_size;
    static EncodeTiledFn enc = nullptr;
    static void *xn, *kvT, *hbuf, *y2T, *flags, *stats;
    if (!enc) {
        void* fn = nullptr;
        cudaDriverEntryPointQueryResult qr;
        cudaGetDriverEntryPoint("cuTensorMapEncodeTiled", &fn, cudaEnableDefault, &qr);
        enc = (EncodeTiledFn)fn;
        cudaGetSymbolAddress(&xn, g_xn);
        cudaGetSymbolAddress(&kvT, g_kvT);
        cudaGetSymbolAddress(&hbuf, g_h);
        cudaGetSymbolAddress(&y2T, g_y2T);
        cudaGetSymbolAddress(&flags, g_flags);
        cudaGetSymbolAddress(&stats, g_stats);
        cudaFuncSetAttribute(h3_kernel, cudaFuncAttributeMaxDynamicSharedMemorySize, SMEM_BYTES);
    }
    Params p;
    const bf16* q = (const bf16*)d_in[0];
    p.q = q; p.k = (const bf16*)d_in[1]; p.v = (const bf16*)d_in[2];
    p.shift_k = (const bf16*)d_in[3]; p.ssm_k = (const bf16*)d_in[4]; p.ssm_D = (const bf16*)d_in[5];
    const bf16* wg = (const bf16*)d_in[7];
    const bf16* wu = (const bf16*)d_in[8];
    const bf16* wd = (const bf16*)d_in[9];
    p.xn = (bf16*)xn; p.kvT = (bf16*)kvT; p.y2T = (bf16*)y2T; p.flags = (unsigned*)flags; p.stats = (uint2*)stats;
    p.dbg = g_dbg_ptr;
    map2d(enc, &p.tmXn128, xn, D, S, 128);
    map2d(enc, &p.tmXn64, xn, D, S, 64);
    map3d(enc, &p.tmWg2, wg, F, D, 2);
    map3d(enc, &p.tmWu2, wu, F, D, 2);
    map3d(enc, &p.tmWg1, wg, F, D, 1);
    map3d(enc, &p.tmWu1, wu, F, D, 1);
    map2d(enc, &p.tmH64, hbuf, F, S, 64);
    map3d(enc, &p.tmWd, wd, D, F, 2);
    map2d(enc, &p.tmX128, q, D, S, 128);
    map2d(enc, &p.tmY2T, y2T, S, D, 128);
    map2d(enc, &p.tmOut64, d_out, D, S, 64);
    {
        const uint64_t d[2] = {D, S}, st[1] = {D * 2};
        const uint32_t bk[2] = {128, 67}, bv[2] = {128, 64};
        make_map(enc, &p.tmK, p.k, 2, d, st, bk, CU_TENSOR_MAP_SWIZZLE_NONE);
        make_map(enc, &p.tmV, p.v, 2, d, st, bv, CU_TENSOR_MAP_SWIZZLE_NONE);
    }
    map2d(enc, &p.tmKvT, kvT, S, D, 128);

    cudaLaunchConfig_t cfg = {};
    cfg.gridDim = dim3(NCTA + 4);
    cfg.blockDim = dim3(384);
    cfg.dynamicSmemBytes = SMEM_BYTES;
    cfg.stream = cudaStreamPerThread;
    cudaLaunchAttribute at[1];
    at[0].id = cudaLaunchAttributeClusterDimension;
    at[0].val.clusterDim.x = 2; at[0].val.clusterDim.y = 1; at[0].val.clusterDim.z = 1;
    cfg.attrs = at; cfg.numAttrs = 1;
    cudaLaunchKernelEx(&cfg, h3_kernel, p);
}
```

```cpp
#include <cuda_runtime.h>
#include <cuda_bf16.h>
#include <cuda.h>
#include <stdint.h>
#include <stdio.h>

namespace h3 {

typedef __nv_bfloat16 bf16;

constexpr int S = 2048;
constexpr int D = 1024;
constexpr int F = 3584;
constexpr int NCTA = 128;

__device__ __align__(1024) bf16 g_xn[S * D];
__device__ __align__(1024) bf16 g_kvT[D * S];
__device__ __align__(1024) bf16 g_h[S * F];
__device__ __align__(1024) bf16 g_y2T[D * S];
__device__ __align__(1024) uint2 g_stats[S];
constexpr int FLAG_STRIDE = 32;
constexpr int FL_XN = 0, FL_H = 16, FL_Y = 32, FL_KV = 40, FL_DONE = 41, FL_H2 = 42, FL_COUNT = 58;
__device__ __align__(1024) unsigned g_flags[FL_COUNT * FLAG_STRIDE];

struct alignas(64) Params {
    CUtensorMap tmXn128;
    CUtensorMap tmXn64;
    CUtensorMap tmWg2;
    CUtensorMap tmWu2;
    CUtensorMap tmWg1;
    CUtensorMap tmWu1;
    CUtensorMap tmH64;
    CUtensorMap tmWd;
    CUtensorMap tmX128;
    CUtensorMap tmY2T;
    CUtensorMap tmOut64;
    CUtensorMap tmK;
    CUtensorMap tmV;
    CUtensorMap tmKvT;
    const bf16* q; const bf16* k; const bf16* v; const bf16* shift_k; const bf16* ssm_k; const bf16* ssm_D;
    bf16* xn; bf16* kvT; bf16* y2T; uint2* stats;
    unsigned* flags;
};

constexpr uint32_t RING_BYTES = 196608;
constexpr uint32_t A_STAGE = 49152, B_STAGE = 32768;
constexpr uint32_t OFF_STG = RING_BYTES + 1024;
constexpr uint32_t OFF_BAR = OFF_STG + 32768;
constexpr uint32_t BAR_FULLA = 0, BAR_EMPTYA = 32, BAR_FULLB = 96, BAR_EMPTYB = 144,
                   BAR_STGFULL = 200, BAR_STGEMPTY = 208, BAR_ALTFULL = 216, BAR_OPFULL = 232,
                   BAR_ALT2FULL = 240, OFF_STAT = 256;
constexpr uint32_t SMEM_BYTES = OFF_BAR + 512 + 1024;

constexpr int ST_H = 4, ST_U = 5, ST_C0 = 0, ST_C1 = 1, ST_ALT = 2, ST_ALT2 = 3;
constexpr uint32_t U_PITCH = 4096 + 128;

__device__ __forceinline__ uint32_t smem_u32(const void* p) { return (uint32_t)__cvta_generic_to_shared(p); }
__device__ __forceinline__ uint64_t make_desc(uint32_t addr, uint32_t lbo, uint32_t sbo) {
    uint64_t d = (uint64_t)((addr & 0x3FFFF) >> 4);
    d |= (uint64_t)((lbo & 0x3FFFF) >> 4) << 16;
    d |= (uint64_t)((sbo & 0x3FFFF) >> 4) << 32;
    d |= (uint64_t)1 << 62;
    return d;
}
__device__ __forceinline__ uint64_t make_desc_noswz(uint32_t addr, uint32_t lbo, uint32_t sbo) {
    return (uint64_t)((addr & 0x3FFFF) >> 4) | ((uint64_t)(lbo >> 4) << 16) | ((uint64_t)(sbo >> 4) << 32);
}
constexpr uint32_t WAIT_LIMIT = 1u << 27;
__device__ __forceinline__ void mbar_init(uint32_t bar, uint32_t count) { asm volatile("mbarrier.init.shared::cta.b64 [%0], %1;" :: "r"(bar), "r"(count) : "memory"); }
__device__ __forceinline__ void mbar_expect_tx(uint32_t bar, uint32_t bytes) { asm volatile("mbarrier.arrive.expect_tx.shared::cta.b64 _, [%0], %1;" :: "r"(bar), "r"(bytes) : "memory"); }
__device__ __forceinline__ void mbar_arrive(uint32_t bar) { asm volatile("mbarrier.arrive.shared::cta.b64 _, [%0];" :: "r"(bar) : "memory"); }
__device__ __forceinline__ void mbar_arrive_cta(uint32_t bar, uint32_t cta) {
    asm volatile("{\n.reg .b32 ra;\nmapa.shared::cluster.u32 ra, %0, %1;\nmbarrier.arrive.shared::cluster.b64 _, [ra];\n}" :: "r"(bar), "r"(cta) : "memory");
}
__device__ __forceinline__ uint32_t mbar_try(uint32_t bar, uint32_t parity) {
    uint32_t ok;
    asm volatile("{\n.reg .pred p;\nmbarrier.try_wait.parity.shared::cta.b64 p, [%1], %2;\nselp.u32 %0, 1, 0, p;\n}" : "=r"(ok) : "r"(bar), "r"(parity) : "memory");
    return ok;
}
__device__ __forceinline__ void mbar_wait(uint32_t bar, uint32_t parity) {
    if (!mbar_try(bar, parity)) {
        const uint32_t t0 = (uint32_t)clock();
        while (!mbar_try(bar, parity) && (uint32_t)clock() - t0 < WAIT_LIMIT) {}
    }
}
__device__ __forceinline__ void mbar_wait_idle(uint32_t bar, uint32_t parity) {
    const uint32_t t0 = (uint32_t)clock();
    while (!mbar_try(bar, parity) && (uint32_t)clock() - t0 < WAIT_LIMIT) {
        __nanosleep(256);
    }
}
__device__ __forceinline__ void flag_wait(const unsigned* f, unsigned target) {
    const uint32_t t0 = (uint32_t)clock();
    unsigned v;
    do {
        asm volatile("ld.acquire.gpu.global.u32 %0, [%1];" : "=r"(v) : "l"(f) : "memory");
    } while (v < target && (uint32_t)clock() - t0 < WAIT_LIMIT);
}
__device__ __forceinline__ void flag_add_after_bulk(unsigned* f) {
    asm volatile("red.relaxed.gpu.global.add.u32 [%0], 1;" :: "l"(f) : "memory");
}
__device__ __forceinline__ void cluster_arrive() { asm volatile("barrier.cluster.arrive.relaxed;" ::: "memory"); }
__device__ __forceinline__ void cluster_wait() { asm volatile("barrier.cluster.wait.acquire;" ::: "memory"); }
__device__ __forceinline__ void tma_2d(uint32_t dst, const CUtensorMap* m, int c0, int c1, uint32_t bar) {
    asm volatile("cp.async.bulk.tensor.2d.shared::cluster.global.mbarrier::complete_tx::bytes [%0], [%1, {%3, %4}], [%2];"
        :: "r"(dst), "l"(m), "r"(bar), "r"(c0), "r"(c1) : "memory");
}
__device__ __forceinline__ void tma_2d_mc(uint32_t dst, const CUtensorMap* m, int c0, int c1, uint32_t bar) {
    asm volatile("cp.async.bulk.tensor.2d.shared::cluster.global.mbarrier::complete_tx::bytes.multicast::cluster [%0], [%1, {%3, %4}], [%2], %5;"
        :: "r"(dst), "l"(m), "r"(bar), "r"(c0), "r"(c1), "h"((uint16_t)3) : "memory");
}
__device__ __forceinline__ void tma_3d(uint32_t dst, const CUtensorMap* m, int c0, int c1, int c2, uint32_t bar) {
    asm volatile("cp.async.bulk.tensor.3d.shared::cluster.global.mbarrier::complete_tx::bytes [%0], [%1, {%3, %4, %5}], [%2];"
        :: "r"(dst), "l"(m), "r"(bar), "r"(c0), "r"(c1), "r"(c2) : "memory");
}
__device__ __forceinline__ uint64_t policy_evict_first() {
    uint64_t pol; asm volatile("createpolicy.fractional.L2::evict_first.b64 %0, 1.0;" : "=l"(pol)); return pol;
}
__device__ __forceinline__ void tma_3d_h(uint32_t dst, const CUtensorMap* m, int c0, int c1, int c2, uint32_t bar, uint64_t pol) {
    asm volatile("cp.async.bulk.tensor.3d.shared::cluster.global.mbarrier::complete_tx::bytes.L2::cache_hint [%0], [%1, {%3, %4, %5}], [%2], %6;"
        :: "r"(dst), "l"(m), "r"(bar), "r"(c0), "r"(c1), "r"(c2), "l"(pol) : "memory");
}
__device__ __forceinline__ void tma_2d_h(uint32_t dst, const CUtensorMap* m, int c0, int c1, uint32_t bar, uint64_t pol) {
    asm volatile("cp.async.bulk.tensor.2d.shared::cluster.global.mbarrier::complete_tx::bytes.L2::cache_hint [%0], [%1, {%3, %4}], [%2], %5;"
        :: "r"(dst), "l"(m), "r"(bar), "r"(c0), "r"(c1), "l"(pol) : "memory");
}
__device__ __forceinline__ void pf_bulk_h(const void* src, uint32_t bytes, uint64_t pol) {
    asm volatile("cp.async.bulk.prefetch.L2.global.L2::cache_hint [%0], %1, %2;" :: "l"(src), "r"(bytes), "l"(pol) : "memory");
}
__device__ __forceinline__ void tma_3d_mc_h(uint32_t dst, const CUtensorMap* m, int c0, int c1, int c2, uint32_t bar, uint64_t pol) {
    asm volatile("cp.async.bulk.tensor.3d.shared::cluster.global.mbarrier::complete_tx::bytes.multicast::cluster.L2::cache_hint [%0], [%1, {%3, %4, %5}], [%2], %6, %7;"
        :: "r"(dst), "l"(m), "r"(bar), "r"(c0), "r"(c1), "r"(c2), "h"((uint16_t)3), "l"(pol) : "memory");
}
__device__ __forceinline__ void bulk_g2s_h(uint32_t dst, const void* src, uint32_t bytes, uint32_t bar, uint64_t pol) {
    asm volatile("cp.async.bulk.shared::cluster.global.mbarrier::complete_tx::bytes.L2::cache_hint [%0], [%1], %2, [%3], %4;"
        :: "r"(dst), "l"(src), "r"(bytes), "r"(bar), "l"(pol) : "memory");
}
__device__ __forceinline__ void bulk_s2g(void* dst, uint32_t src, uint32_t bytes) {
    asm volatile("cp.async.bulk.global.shared::cta.bulk_group [%0], [%1], %2;" :: "l"(dst), "r"(src), "r"(bytes) : "memory");
}
__device__ __forceinline__ void tma_store_2d(const CUtensorMap* m, uint32_t src, int c0, int c1) {
    asm volatile("cp.async.bulk.tensor.2d.global.shared::cta.bulk_group [%0, {%2, %3}], [%1];"
        :: "l"(m), "r"(src), "r"(c0), "r"(c1) : "memory");
}
__device__ __forceinline__ void pf_2d(const CUtensorMap* m, int c0, int c1) {
    asm volatile("cp.async.bulk.prefetch.tensor.2d.L2.global.tile [%0, {%1, %2}];" :: "l"(m), "r"(c0), "r"(c1) : "memory");
}
__device__ __forceinline__ void pf_bulk(const void* src, uint32_t bytes) {
    asm volatile("cp.async.bulk.prefetch.L2.global [%0], %1;" :: "l"(src), "r"(bytes) : "memory");
}
__device__ __forceinline__ void bulk_commit() { asm volatile("cp.async.bulk.commit_group;" ::: "memory"); }
__device__ __forceinline__ void bulk_wait_read() { asm volatile("cp.async.bulk.wait_group.read 0;" ::: "memory"); }
__device__ __forceinline__ void bulk_wait_all() { asm volatile("cp.async.bulk.wait_group 0;" ::: "memory"); }
__device__ __forceinline__ void fence_async_smem() { asm volatile("fence.proxy.async.shared::cta;" ::: "memory"); }
__device__ __forceinline__ void bar_sync(int id, int n) { asm volatile("bar.sync %0, %1;" :: "r"(id), "r"(n) : "memory"); }
__device__ __forceinline__ void bar_arrive(int id, int n) { asm volatile("bar.arrive %0, %1;" :: "r"(id), "r"(n) : "memory"); }
__device__ __forceinline__ void cluster_sync() {
    asm volatile("barrier.cluster.arrive.release.aligned;" ::: "memory");
    asm volatile("barrier.cluster.wait.acquire.aligned;" ::: "memory");
}
__device__ __forceinline__ void wg_fence() { asm volatile("wgmma.fence.sync.aligned;" ::: "memory"); }
__device__ __forceinline__ void wg_commit() { asm volatile("wgmma.commit_group.sync.aligned;" ::: "memory"); }
template <int N> __device__ __forceinline__ void wg_wait() { asm volatile("wgmma.wait_group.sync.aligned %0;" :: "n"(N) : "memory"); }

#define H3_R4(b)  "+f"(d[b+0]), "+f"(d[b+1]), "+f"(d[b+2]), "+f"(d[b+3])
#define H3_R8(b)  H3_R4(b), H3_R4(b+4)
#define H3_R16(b) H3_R8(b), H3_R8(b+8)
#define H3_R32(b) H3_R16(b), H3_R16(b+16)
#define H3_R64(b) H3_R32(b), H3_R32(b+32)

__device__ __forceinline__ void wgmma_256(float (&d)[128], uint64_t a, uint64_t b, int scale_d) {
    asm volatile("{\n.reg .pred p;\nsetp.ne.b32 p, %130, 0;\n"
    "wgmma.mma_async.sync.aligned.m64n256k16.f32.bf16.bf16 "
    "{%0,%1,%2,%3,%4,%5,%6,%7,%8,%9,%10,%11,%12,%13,%14,%15,"
    "%16,%17,%18,%19,%20,%21,%22,%23,%24,%25,%26,%27,%28,%29,%30,%31,"
    "%32,%33,%34,%35,%36,%37,%38,%39,%40,%41,%42,%43,%44,%45,%46,%47,"
    "%48,%49,%50,%51,%52,%53,%54,%55,%56,%57,%58,%59,%60,%61,%62,%63,"
    "%64,%65,%66,%67,%68,%69,%70,%71,%72,%73,%74,%75,%76,%77,%78,%79,"
    "%80,%81,%82,%83,%84,%85,%86,%87,%88,%89,%90,%91,%92,%93,%94,%95,"
    "%96,%97,%98,%99,%100,%101,%102,%103,%104,%105,%106,%107,%108,%109,%110,%111,"
    "%112,%113,%114,%115,%116,%117,%118,%119,%120,%121,%122,%123,%124,%125,%126,%127},"
    "%128, %129, p, 1, 1, 0, 1;\n}\n"
    : H3_R64(0), H3_R64(64)
    : "l"(a), "l"(b), "r"(scale_d));
}
__device__ __forceinline__ void wgmma_128(float (&d)[64], uint64_t a, uint64_t b, int scale_d) {
    asm volatile("{\n.reg .pred p;\nsetp.ne.b32 p, %66, 0;\n"
    "wgmma.mma_async.sync.aligned.m64n128k16.f32.bf16.bf16 "
    "{%0,%1,%2,%3,%4,%5,%6,%7,%8,%9,%10,%11,%12,%13,%14,%15,"
    "%16,%17,%18,%19,%20,%21,%22,%23,%24,%25,%26,%27,%28,%29,%30,%31,"
    "%32,%33,%34,%35,%36,%37,%38,%39,%40,%41,%42,%43,%44,%45,%46,%47,"
    "%48,%49,%50,%51,%52,%53,%54,%55,%56,%57,%58,%59,%60,%61,%62,%63},"
    "%64, %65, p, 1, 1, 0, 1;\n}\n"
    : H3_R64(0)
    : "l"(a), "l"(b), "r"(scale_d));
}
__device__ __forceinline__ void ldsm_x4(uint32_t addr, uint32_t& r0, uint32_t& r1, uint32_t& r2, uint32_t& r3) {
    asm volatile("ldmatrix.sync.aligned.m8n8.x4.shared.b16 {%0,%1,%2,%3}, [%4];" : "=r"(r0), "=r"(r1), "=r"(r2), "=r"(r3) : "r"(addr) : "memory");
}
__device__ __forceinline__ void ldsm_x4_t(uint32_t addr, uint32_t& r0, uint32_t& r1, uint32_t& r2, uint32_t& r3) {
    asm volatile("ldmatrix.sync.aligned.m8n8.x4.trans.shared.b16 {%0,%1,%2,%3}, [%4];" : "=r"(r0), "=r"(r1), "=r"(r2), "=r"(r3) : "r"(addr) : "memory");
}
__device__ __forceinline__ void stsm_x4(uint32_t addr, uint32_t r0, uint32_t r1, uint32_t r2, uint32_t r3) {
    asm volatile("stmatrix.sync.aligned.m8n8.x4.shared.b16 [%0], {%1,%2,%3,%4};" :: "r"(addr), "r"(r0), "r"(r1), "r"(r2), "r"(r3) : "memory");
}
template <int OFF> __device__ __forceinline__ uint32_t lds32_o(uint32_t addr) { uint32_t v; asm volatile("ld.shared.b32 %0, [%1+%2];" : "=r"(v) : "r"(addr), "n"(OFF) : "memory"); return v; }
__device__ __forceinline__ uint32_t lds32(uint32_t addr) { uint32_t v; asm volatile("ld.shared.b32 %0, [%1];" : "=r"(v) : "r"(addr) : "memory"); return v; }
__device__ __forceinline__ uint4 lds128(uint32_t addr) { uint4 v; asm volatile("ld.shared.v4.b32 {%0,%1,%2,%3}, [%4];" : "=r"(v.x), "=r"(v.y), "=r"(v.z), "=r"(v.w) : "r"(addr) : "memory"); return v; }
__device__ __forceinline__ void sts128(uint32_t addr, uint32_t a, uint32_t b, uint32_t c, uint32_t d) { asm volatile("st.shared.v4.b32 [%0], {%1,%2,%3,%4};" :: "r"(addr), "r"(a), "r"(b), "r"(c), "r"(d) : "memory"); }

__device__ __forceinline__ uint32_t bf2_mul(uint32_t a, uint32_t b) { uint32_t r; asm("mul.rn.bf16x2 %0, %1, %2;" : "=r"(r) : "r"(a), "r"(b)); return r; }
__device__ __forceinline__ uint32_t bf2_add(uint32_t a, uint32_t b) { uint32_t r; asm("add.rn.bf16x2 %0, %1, %2;" : "=r"(r) : "r"(a), "r"(b)); return r; }
__device__ __forceinline__ uint32_t bf2_sub(uint32_t a, uint32_t b) { uint32_t r; asm("sub.rn.bf16x2 %0, %1, %2;" : "=r"(r) : "r"(a), "r"(b)); return r; }
__device__ __forceinline__ uint32_t pack_bf2(float lo, float hi) { uint32_t r; asm("cvt.rn.bf16x2.f32 %0, %1, %2;" : "=r"(r) : "f"(hi), "f"(lo)); return r; }
__device__ __forceinline__ float bf_lo(uint32_t v) { return __uint_as_float(v << 16); }
__device__ __forceinline__ float bf_hi(uint32_t v) { return __uint_as_float(v & 0xFFFF0000u); }
__device__ __forceinline__ float silu_f(float x) {
    float e, r;
    asm("ex2.approx.ftz.f32 %0, %1;" : "=f"(e) : "f"(x * -1.4426950408889634f));
    asm("rcp.approx.ftz.f32 %0, %1;" : "=f"(r) : "f"(1.0f + e));
    return x * r;
}
__device__ __forceinline__ uint32_t silu_bf2(uint32_t v) { return pack_bf2(silu_f(bf_lo(v)), silu_f(bf_hi(v))); }


template <int I>
__device__ __forceinline__ void stage_piece(const uint32_t (&pg)[32], const uint32_t (&pu)[32], uint32_t stg_lane, uint32_t lrow7, uint32_t lgrp) {
    const uint32_t addr = stg_lane + (((2 * (I & 3) + lgrp) ^ lrow7) << 4);
    stsm_x4(addr, pg[4 * I], pg[4 * I + 1], pg[4 * I + 2], pg[4 * I + 3]);
    stsm_x4(addr + 8192, pu[4 * I], pu[4 * I + 1], pu[4 * I + 2], pu[4 * I + 3]);
}
__device__ __forceinline__ void stage_piece_dyn(int i, const uint32_t (&pg)[32], const uint32_t (&pu)[32], uint32_t stg_lane, uint32_t lrow7, uint32_t lgrp) {
    switch (i) {
        case 0: stage_piece<0>(pg, pu, stg_lane, lrow7, lgrp); break;
        case 1: stage_piece<1>(pg, pu, stg_lane, lrow7, lgrp); break;
        case 2: stage_piece<2>(pg, pu, stg_lane, lrow7, lgrp); break;
        case 3: stage_piece<3>(pg, pu, stg_lane, lrow7, lgrp); break;
        case 4: stage_piece<4>(pg, pu, stg_lane, lrow7, lgrp); break;
        case 5: stage_piece<5>(pg, pu, stg_lane, lrow7, lgrp); break;
        case 6: stage_piece<6>(pg, pu, stg_lane, lrow7, lgrp); break;
        default: stage_piece<7>(pg, pu, stg_lane, lrow7, lgrp); break;
    }
}
__device__ __forceinline__ void wgmma_128_lo(float (&d)[128], uint64_t a, uint64_t b, int scale_d) {
    asm volatile("{\n.reg .pred p;\nsetp.ne.b32 p, %66, 0;\n"
    "wgmma.mma_async.sync.aligned.m64n128k16.f32.bf16.bf16 "
    "{%0,%1,%2,%3,%4,%5,%6,%7,%8,%9,%10,%11,%12,%13,%14,%15,"
    "%16,%17,%18,%19,%20,%21,%22,%23,%24,%25,%26,%27,%28,%29,%30,%31,"
    "%32,%33,%34,%35,%36,%37,%38,%39,%40,%41,%42,%43,%44,%45,%46,%47,"
    "%48,%49,%50,%51,%52,%53,%54,%55,%56,%57,%58,%59,%60,%61,%62,%63},"
    "%64, %65, p, 1, 1, 0, 1;\n}\n"
    : H3_R64(0)
    : "l"(a), "l"(b), "r"(scale_d));
}

template <int N> __device__ __forceinline__ void wgmma_rs(float (&d)[128], const uint32_t (&a)[4], uint64_t b, int scale_d);
template <> __device__ __forceinline__ void wgmma_rs<64>(float (&d)[128], const uint32_t (&a)[4], uint64_t b, int scale_d) {
    asm volatile("{\n.reg .pred p;\nsetp.ne.b32 p, %37, 0;\nwgmma.mma_async.sync.aligned.m64n64k16.f32.bf16.bf16 {%0,%1,%2,%3,%4,%5,%6,%7,%8,%9,%10,%11,%12,%13,%14,%15,%16,%17,%18,%19,%20,%21,%22,%23,%24,%25,%26,%27,%28,%29,%30,%31}, {%32,%33,%34,%35}, %36, p, 1, 1, 0;\n}\n"
        : "+f"(d[0]), "+f"(d[1]), "+f"(d[2]), "+f"(d[3]), "+f"(d[4]), "+f"(d[5]), "+f"(d[6]), "+f"(d[7]), "+f"(d[8]), "+f"(d[9]), "+f"(d[10]), "+f"(d[11]), "+f"(d[12]), "+f"(d[13]), "+f"(d[14]), "+f"(d[15]), "+f"(d[16]), "+f"(d[17]), "+f"(d[18]), "+f"(d[19]), "+f"(d[20]), "+f"(d[21]), "+f"(d[22]), "+f"(d[23]), "+f"(d[24]), "+f"(d[25]), "+f"(d[26]), "+f"(d[27]), "+f"(d[28]), "+f"(d[29]), "+f"(d[30]), "+f"(d[31])
        : "r"(a[0]), "r"(a[1]), "r"(a[2]), "r"(a[3]), "l"(b), "r"(scale_d));
}
template <> __device__ __forceinline__ void wgmma_rs<128>(float (&d)[128], const uint32_t (&a)[4], uint64_t b, int scale_d) {
    asm volatile("{\n.reg .pred p;\nsetp.ne.b32 p, %69, 0;\nwgmma.mma_async.sync.aligned.m64n128k16.f32.bf16.bf16 {%0,%1,%2,%3,%4,%5,%6,%7,%8,%9,%10,%11,%12,%13,%14,%15,%16,%17,%18,%19,%20,%21,%22,%23,%24,%25,%26,%27,%28,%29,%30,%31,%32,%33,%34,%35,%36,%37,%38,%39,%40,%41,%42,%43,%44,%45,%46,%47,%48,%49,%50,%51,%52,%53,%54,%55,%56,%57,%58,%59,%60,%61,%62,%63}, {%64,%65,%66,%67}, %68, p, 1, 1, 0;\n}\n"
        : "+f"(d[0]), "+f"(d[1]), "+f"(d[2]), "+f"(d[3]), "+f"(d[4]), "+f"(d[5]), "+f"(d[6]), "+f"(d[7]), "+f"(d[8]), "+f"(d[9]), "+f"(d[10]), "+f"(d[11]), "+f"(d[12]), "+f"(d[13]), "+f"(d[14]), "+f"(d[15]), "+f"(d[16]), "+f"(d[17]), "+f"(d[18]), "+f"(d[19]), "+f"(d[20]), "+f"(d[21]), "+f"(d[22]), "+f"(d[23]), "+f"(d[24]), "+f"(d[25]), "+f"(d[26]), "+f"(d[27]), "+f"(d[28]), "+f"(d[29]), "+f"(d[30]), "+f"(d[31]), "+f"(d[32]), "+f"(d[33]), "+f"(d[34]), "+f"(d[35]), "+f"(d[36]), "+f"(d[37]), "+f"(d[38]), "+f"(d[39]), "+f"(d[40]), "+f"(d[41]), "+f"(d[42]), "+f"(d[43]), "+f"(d[44]), "+f"(d[45]), "+f"(d[46]), "+f"(d[47]), "+f"(d[48]), "+f"(d[49]), "+f"(d[50]), "+f"(d[51]), "+f"(d[52]), "+f"(d[53]), "+f"(d[54]), "+f"(d[55]), "+f"(d[56]), "+f"(d[57]), "+f"(d[58]), "+f"(d[59]), "+f"(d[60]), "+f"(d[61]), "+f"(d[62]), "+f"(d[63])
        : "r"(a[0]), "r"(a[1]), "r"(a[2]), "r"(a[3]), "l"(b), "r"(scale_d));
}
template <> __device__ __forceinline__ void wgmma_rs<192>(float (&d)[128], const uint32_t (&a)[4], uint64_t b, int scale_d) {
    asm volatile("{\n.reg .pred p;\nsetp.ne.b32 p, %101, 0;\nwgmma.mma_async.sync.aligned.m64n192k16.f32.bf16.bf16 {%0,%1,%2,%3,%4,%5,%6,%7,%8,%9,%10,%11,%12,%13,%14,%15,%16,%17,%18,%19,%20,%21,%22,%23,%24,%25,%26,%27,%28,%29,%30,%31,%32,%33,%34,%35,%36,%37,%38,%39,%40,%41,%42,%43,%44,%45,%46,%47,%48,%49,%50,%51,%52,%53,%54,%55,%56,%57,%58,%59,%60,%61,%62,%63,%64,%65,%66,%67,%68,%69,%70,%71,%72,%73,%74,%75,%76,%77,%78,%79,%80,%81,%82,%83,%84,%85,%86,%87,%88,%89,%90,%91,%92,%93,%94,%95}, {%96,%97,%98,%99}, %100, p, 1, 1, 0;\n}\n"
        : "+f"(d[0]), "+f"(d[1]), "+f"(d[2]), "+f"(d[3]), "+f"(d[4]), "+f"(d[5]), "+f"(d[6]), "+f"(d[7]), "+f"(d[8]), "+f"(d[9]), "+f"(d[10]), "+f"(d[11]), "+f"(d[12]), "+f"(d[13]), "+f"(d[14]), "+f"(d[15]), "+f"(d[16]), "+f"(d[17]), "+f"(d[18]), "+f"(d[19]), "+f"(d[20]), "+f"(d[21]), "+f"(d[22]), "+f"(d[23]), "+f"(d[24]), "+f"(d[25]), "+f"(d[26]), "+f"(d[27]), "+f"(d[28]), "+f"(d[29]), "+f"(d[30]), "+f"(d[31]), "+f"(d[32]), "+f"(d[33]), "+f"(d[34]), "+f"(d[35]), "+f"(d[36]), "+f"(d[37]), "+f"(d[38]), "+f"(d[39]), "+f"(d[40]), "+f"(d[41]), "+f"(d[42]), "+f"(d[43]), "+f"(d[44]), "+f"(d[45]), "+f"(d[46]), "+f"(d[47]), "+f"(d[48]), "+f"(d[49]), "+f"(d[50]), "+f"(d[51]), "+f"(d[52]), "+f"(d[53]), "+f"(d[54]), "+f"(d[55]), "+f"(d[56]), "+f"(d[57]), "+f"(d[58]), "+f"(d[59]), "+f"(d[60]), "+f"(d[61]), "+f"(d[62]), "+f"(d[63]), "+f"(d[64]), "+f"(d[65]), "+f"(d[66]), "+f"(d[67]), "+f"(d[68]), "+f"(d[69]), "+f"(d[70]), "+f"(d[71]), "+f"(d[72]), "+f"(d[73]), "+f"(d[74]), "+f"(d[75]), "+f"(d[76]), "+f"(d[77]), "+f"(d[78]), "+f"(d[79]), "+f"(d[80]), "+f"(d[81]), "+f"(d[82]), "+f"(d[83]), "+f"(d[84]), "+f"(d[85]), "+f"(d[86]), "+f"(d[87]), "+f"(d[88]), "+f"(d[89]), "+f"(d[90]), "+f"(d[91]), "+f"(d[92]), "+f"(d[93]), "+f"(d[94]), "+f"(d[95])
        : "r"(a[0]), "r"(a[1]), "r"(a[2]), "r"(a[3]), "l"(b), "r"(scale_d));
}
template <> __device__ __forceinline__ void wgmma_rs<256>(float (&d)[128], const uint32_t (&a)[4], uint64_t b, int scale_d) {
    asm volatile("{\n.reg .pred p;\nsetp.ne.b32 p, %133, 0;\nwgmma.mma_async.sync.aligned.m64n256k16.f32.bf16.bf16 {%0,%1,%2,%3,%4,%5,%6,%7,%8,%9,%10,%11,%12,%13,%14,%15,%16,%17,%18,%19,%20,%21,%22,%23,%24,%25,%26,%27,%28,%29,%30,%31,%32,%33,%34,%35,%36,%37,%38,%39,%40,%41,%42,%43,%44,%45,%46,%47,%48,%49,%50,%51,%52,%53,%54,%55,%56,%57,%58,%59,%60,%61,%62,%63,%64,%65,%66,%67,%68,%69,%70,%71,%72,%73,%74,%75,%76,%77,%78,%79,%80,%81,%82,%83,%84,%85,%86,%87,%88,%89,%90,%91,%92,%93,%94,%95,%96,%97,%98,%99,%100,%101,%102,%103,%104,%105,%106,%107,%108,%109,%110,%111,%112,%113,%114,%115,%116,%117,%118,%119,%120,%121,%122,%123,%124,%125,%126,%127}, {%128,%129,%130,%131}, %132, p, 1, 1, 0;\n}\n"
        : "+f"(d[0]), "+f"(d[1]), "+f"(d[2]), "+f"(d[3]), "+f"(d[4]), "+f"(d[5]), "+f"(d[6]), "+f"(d[7]), "+f"(d[8]), "+f"(d[9]), "+f"(d[10]), "+f"(d[11]), "+f"(d[12]), "+f"(d[13]), "+f"(d[14]), "+f"(d[15]), "+f"(d[16]), "+f"(d[17]), "+f"(d[18]), "+f"(d[19]), "+f"(d[20]), "+f"(d[21]), "+f"(d[22]), "+f"(d[23]), "+f"(d[24]), "+f"(d[25]), "+f"(d[26]), "+f"(d[27]), "+f"(d[28]), "+f"(d[29]), "+f"(d[30]), "+f"(d[31]), "+f"(d[32]), "+f"(d[33]), "+f"(d[34]), "+f"(d[35]), "+f"(d[36]), "+f"(d[37]), "+f"(d[38]), "+f"(d[39]), "+f"(d[40]), "+f"(d[41]), "+f"(d[42]), "+f"(d[43]), "+f"(d[44]), "+f"(d[45]), "+f"(d[46]), "+f"(d[47]), "+f"(d[48]), "+f"(d[49]), "+f"(d[50]), "+f"(d[51]), "+f"(d[52]), "+f"(d[53]), "+f"(d[54]), "+f"(d[55]), "+f"(d[56]), "+f"(d[57]), "+f"(d[58]), "+f"(d[59]), "+f"(d[60]), "+f"(d[61]), "+f"(d[62]), "+f"(d[63]), "+f"(d[64]), "+f"(d[65]), "+f"(d[66]), "+f"(d[67]), "+f"(d[68]), "+f"(d[69]), "+f"(d[70]), "+f"(d[71]), "+f"(d[72]), "+f"(d[73]), "+f"(d[74]), "+f"(d[75]), "+f"(d[76]), "+f"(d[77]), "+f"(d[78]), "+f"(d[79]), "+f"(d[80]), "+f"(d[81]), "+f"(d[82]), "+f"(d[83]), "+f"(d[84]), "+f"(d[85]), "+f"(d[86]), "+f"(d[87]), "+f"(d[88]), "+f"(d[89]), "+f"(d[90]), "+f"(d[91]), "+f"(d[92]), "+f"(d[93]), "+f"(d[94]), "+f"(d[95]), "+f"(d[96]), "+f"(d[97]), "+f"(d[98]), "+f"(d[99]), "+f"(d[100]), "+f"(d[101]), "+f"(d[102]), "+f"(d[103]), "+f"(d[104]), "+f"(d[105]), "+f"(d[106]), "+f"(d[107]), "+f"(d[108]), "+f"(d[109]), "+f"(d[110]), "+f"(d[111]), "+f"(d[112]), "+f"(d[113]), "+f"(d[114]), "+f"(d[115]), "+f"(d[116]), "+f"(d[117]), "+f"(d[118]), "+f"(d[119]), "+f"(d[120]), "+f"(d[121]), "+f"(d[122]), "+f"(d[123]), "+f"(d[124]), "+f"(d[125]), "+f"(d[126]), "+f"(d[127])
        : "r"(a[0]), "r"(a[1]), "r"(a[2]), "r"(a[3]), "l"(b), "r"(scale_d));
}

template <int I> __device__ __forceinline__ void conv_load_a(uint32_t (&a)[16][4], const uint32_t (&hx)[8]) {
    constexpr int IP = I >> 2, SG = I & 3;
    a[I][0] = lds32_o<-1024 * IP>(hx[2 * SG]); a[I][1] = lds32_o<-1024 * IP - 512>(hx[2 * SG]);
    a[I][2] = lds32_o<-1024 * IP>(hx[2 * SG + 1]); a[I][3] = lds32_o<-1024 * IP - 512>(hx[2 * SG + 1]);
    if constexpr (I < 15) conv_load_a<I + 1>(a, hx);
}
template <int I> __device__ __forceinline__ void conv_issue(float (&acc)[128], const uint32_t (&a)[16][4], uint64_t db) {
    wgmma_rs<256 - 64 * (I >> 2)>(acc, a[I], db + 64 * (I >> 2) + 2 * (I & 3), I != 0);
    if constexpr (I < 15) conv_issue<I + 1>(acc, a, db);
}
__device__ __forceinline__ void conv_frag_addr(uint32_t (&hx)[8], uint32_t copy_base, int w0, uint32_t xb) {
#pragma unroll
    for (int i = 0; i < 8; i++) { const uint32_t W = (uint32_t)(w0 - 4 * i); hx[i] = copy_base + ((W ^ (((W >> 5) & 3u) << 2) ^ xb) << 2); }
}

__device__ __forceinline__ void kv_cta(const Params& p, uint32_t sb, int j) {
    constexpr uint32_t IN_BYTES = 17408 + 16384, OFF_V = 17408;
    constexpr uint32_t OFF_OUT = 4 * IN_BYTES, OFF_TAPS = OFF_OUT + 4 * 16384;
    constexpr uint32_t B_INF = 0, B_INE = 32, B_OUTF = 64, B_OUTE = 96;
    const uint32_t bars = sb + OFF_BAR;
    const int tid = threadIdx.x, lane = tid & 31;
    if (tid == 0) {
        for (int s = 0; s < 4; s++) { mbar_init(bars + B_INF + 8 * s, 1); mbar_init(bars + B_INE + 8 * s, 8); mbar_init(bars + B_OUTF + 8 * s, 8); mbar_init(bars + B_OUTE + 8 * s, 1); }
        asm volatile("fence.mbarrier_init.release.cluster;" ::: "memory");
    }
    for (int i = tid; i < 512; i += 384) { const uint4 t = __ldg(reinterpret_cast<const uint4*>(p.shift_k) + i); sts128(sb + OFF_TAPS + i * 16, t.x, t.y, t.z, t.w); }
    __syncthreads();
    if (tid == 0) {
        const uint64_t pol = policy_evict_first();
#pragma unroll 1
        for (int i = 0; i < 64 + 3; i++) {
            if (i < 64) {
                const int bf = i & 3, t0 = j * 512 + (i >> 3) * 64, c0 = (i & 7) * 128;
                if (i >= 4) mbar_wait(bars + B_INE + 8 * bf, ((i >> 2) - 1) & 1);
                mbar_expect_tx(bars + B_INF + 8 * bf, 67 * 256 + 64 * 256);
                tma_2d_h(sb + bf * IN_BYTES, &p.tmK, c0, t0 - 3, bars + B_INF + 8 * bf, pol);
                tma_2d_h(sb + bf * IN_BYTES + OFF_V, &p.tmV, c0, t0, bars + B_INF + 8 * bf, pol);
            }
            if (i >= 3) {
                const int o = i - 3, bf = o & 3;
                mbar_wait(bars + B_OUTF + 8 * bf, (o >> 2) & 1);
                tma_store_2d(&p.tmKvT, sb + OFF_OUT + bf * 16384, 1984 - (j * 512 + (o >> 3) * 64), (o & 7) * 128);
                bulk_commit();
                asm volatile("cp.async.bulk.wait_group.read 1;" ::: "memory");
                if (o > 0) mbar_arrive(bars + B_OUTE + 8 * ((o - 1) & 3));
            }
        }
        bulk_wait_all();
        flag_add_after_bulk(p.flags + FL_KV * FLAG_STRIDE);
    } else if (tid >= 32) {
#pragma unroll 1
        for (int u = (tid >> 5) - 1; u < 512; u += 11) {
            const int i = u >> 3, bf = i & 3, o = u & 7;
            mbar_wait(bars + B_INF + 8 * bf, (i >> 2) & 1);
            if (i >= 4) mbar_wait(bars + B_OUTE + 8 * bf, ((i >> 2) - 1) & 1);
            const uint32_t out = sb + OFF_OUT + bf * 16384;
            const uint32_t odd = (lane >> 2) & 1, sel0 = odd ? 0x7632u : 0x5410u, sel1 = odd ? 0x5410u : 0x7632u;
            uint32_t kk[2][11], vv[2][8];
            uint4 sw[2];
#pragma unroll
            for (int it = 0; it < 2; it++) {
                const uint32_t rd = sb + bf * IN_BYTES + o * 8 * 256 + (it * 32 + lane) * 4;
#pragma unroll
                for (int r = 0; r < 11; r++) kk[it][r] = lds32(rd + r * 256);
#pragma unroll
                for (int r = 0; r < 8; r++) vv[it][r] = lds32(rd + OFF_V + r * 256);
                sw[it] = lds128(sb + OFF_TAPS + ((i & 7) * 64 + it * 32 + lane) * 16);
            }
#pragma unroll
            for (int it = 0; it < 2; it++) {
                const uint32_t w0 = __byte_perm(sw[it].x, sw[it].z, 0x5410), w1 = __byte_perm(sw[it].x, sw[it].z, 0x7632);
                const uint32_t w2 = __byte_perm(sw[it].y, sw[it].w, 0x5410), w3 = __byte_perm(sw[it].y, sw[it].w, 0x7632);
#pragma unroll
                for (int r = 0; r < 8; r++)
                    vv[it][r] = bf2_mul(bf2_add(bf2_add(bf2_add(bf2_mul(kk[it][r], w3), bf2_mul(kk[it][r + 1], w2)), bf2_mul(kk[it][r + 2], w1)), bf2_mul(kk[it][r + 3], w0)), vv[it][r]);
                const uint32_t r0 = 2 * (it * 32 + lane) + odd, r1 = r0 ^ 1;
                const uint32_t* v = vv[it];
                sts128(out + r0 * 128 + (((7 - o) ^ (r0 & 7)) << 4), __byte_perm(v[0], v[1], sel0), __byte_perm(v[2], v[3], sel0), __byte_perm(v[4], v[5], sel0), __byte_perm(v[6], v[7], sel0));
                sts128(out + r1 * 128 + (((7 - o) ^ (r1 & 7)) << 4), __byte_perm(v[0], v[1], sel1), __byte_perm(v[2], v[3], sel1), __byte_perm(v[4], v[5], sel1), __byte_perm(v[6], v[7], sel1));
            }
            fence_async_smem();
            __syncwarp();
            if (lane == 0) { mbar_arrive(bars + B_INE + 8 * bf); mbar_arrive(bars + B_OUTF + 8 * bf); }
        }
    }
}

__global__ void __launch_bounds__(384, 1) h3_kernel(const __grid_constant__ Params p) {
    extern __shared__ uint8_t smem_raw[];
    const uint32_t sb = (smem_u32(smem_raw) + 1023) & ~1023u;
    const uint32_t bars = sb + OFF_BAR;
    const int tid = threadIdx.x;
    const int wg = __shfl_sync(0xffffffffu, tid >> 7, 0);
    const int lane = tid & 31;
    const int cta = blockIdx.x;
    const int pair = cta >> 1;
    const uint32_t rank = cta & 1;

    if (cta >= NCTA) { kv_cta(p, sb, cta - NCTA); return; }

    uint32_t x[32];
    if (wg != 0) {
        const uint4* src = reinterpret_cast<const uint4*>(p.q + (size_t)(cta * 16 + ((tid >> 5) - 4) * 2 + (lane >> 4)) * D) + (lane & 15);
#pragma unroll
        for (int i = 0; i < 8; i++) { const uint4 t = __ldg(src + i * 16); x[4 * i] = t.x; x[4 * i + 1] = t.y; x[4 * i + 2] = t.z; x[4 * i + 3] = t.w; }
    }
    if (tid == 0) {
#pragma unroll 1
        for (int s = 0; s < 4; s++) { mbar_init(bars + BAR_FULLA + 8 * s, 1); mbar_init(bars + BAR_EMPTYA + 8 * s, 4); }
#pragma unroll 1
        for (int s = 0; s < 6; s++) { mbar_init(bars + BAR_FULLB + 8 * s, 1); mbar_init(bars + BAR_EMPTYB + 8 * s, 4); }
        mbar_init(bars + BAR_STGFULL, 8);
        mbar_init(bars + BAR_STGEMPTY, 1);
        mbar_init(bars + BAR_ALTFULL, 8);
        mbar_init(bars + BAR_ALT2FULL, 8);
        mbar_init(bars + BAR_OPFULL, 1);
        asm volatile("fence.mbarrier_init.release.cluster;" ::: "memory");
    }
    __syncthreads();
    cluster_arrive();

    const int grp = (pair < 4) ? 0 : (pair < 36) ? ((pair - 4) & 7) : 1 + (pair - 36) % 7;
    const int gj = (pair < 4) ? 4 + pair : (pair < 36) ? ((pair - 4) >> 3) : 4 + (pair - 36) / 7;
    const int m1 = 2 * grp + (int)rank, nb1 = gj;
    const int m2 = ((grp >> 2) << 3) | gj, pn = grp & 3;
    const int nh = 24 + pn;
    const int n2 = pn * 256 + (int)rank * 128;

    if (wg == 0) {
        asm volatile("setmaxnreg.dec.sync.aligned.u32 40;\n");
        const int warp = tid >> 5;
        if (warp == 0) {
            if (lane == 0) {
                const uint64_t pol = policy_evict_first();
                const int mrow1 = m1 * 128, mrow2 = m2 * 128 + (int)rank * 64, ngh = nh * 2 + (int)rank;
                const CUtensorMap* tmW = rank ? &p.tmWu2 : &p.tmWg2;
                const uint32_t woff = 16384 + rank * 16384;
                cluster_wait();
#pragma unroll 1
                for (int j = 0; j < 4; j++) {
                    const uint32_t full = bars + BAR_FULLA + 8 * j;
                    mbar_expect_tx(full, A_STAGE);
                    tma_3d_mc_h(sb + j * A_STAGE + woff, tmW, 0, j * 64, nb1 * 2, full, pol);
                }
                flag_wait(p.flags + (FL_XN + m1) * FLAG_STRIDE, 64);
#pragma unroll 1
                for (int j = 0; j < 4; j++) tma_2d(sb + j * A_STAGE, &p.tmXn128, j * 64, mrow1, bars + BAR_FULLA + 8 * j);
#pragma unroll 1
                for (int g = 4; g < 48; g++) {
                    const int st = g & 3, k0 = (g & 15) * 64, ng = ((g >> 4) * 8 + nb1) * 2;
                    const uint32_t full = bars + BAR_FULLA + 8 * st, a = sb + st * A_STAGE;
                    mbar_wait(bars + BAR_EMPTYA + 8 * st, ((g >> 2) - 1) & 1);
                    mbar_expect_tx(full, A_STAGE);
                    tma_2d(a, &p.tmXn128, k0, mrow1, full);
                    tma_3d_mc_h(a + woff, tmW, 0, k0, ng, full, pol);
                    if (g == 3 * ((cta & 31) >> 2) - 2) { pf_bulk_h(p.k + (size_t)cta * 16 * D, 32768, pol); pf_bulk_h(p.v + (size_t)cta * 16 * D, 32768, pol); }
                }
                flag_wait(p.flags + (FL_XN + m2) * FLAG_STRIDE, 64);
                pf_bulk_h(p.ssm_k + (size_t)cta * 8 * S, 32768, pol);
                int st = 0; uint32_t ph = 1;
#pragma unroll 1
                for (int e = 0; e < 16; e++) {
                    const uint32_t full = bars + BAR_FULLB + 8 * st, a = sb + st * B_STAGE;
                    if (e < 6) {
                        if (e != 2 && e != 5) mbar_wait(bars + BAR_EMPTYA + 8 * (e - (e >= 3)), 1);
                    } else {
                        mbar_wait(bars + BAR_EMPTYB + 8 * st, ph);
                    }
                    mbar_expect_tx(full, B_STAGE);
                    tma_2d_mc(a + rank * 8192, &p.tmXn64, e * 64, mrow2, full);
                    tma_3d_h(a + 16384, &p.tmWg1, 0, e * 64, ngh, full, pol);
                    tma_3d_h(a + 24576, &p.tmWu1, 0, e * 64, ngh, full, pol);
                    if (++st == 6) { st = 0; ph ^= 1; }
                }
                mbar_wait(bars + BAR_EMPTYB + 8 * ST_H, 1);
                mbar_expect_tx(bars + BAR_FULLB + 8 * ST_H, 32768);
                bulk_g2s_h(sb + ST_H * B_STAGE, p.ssm_k + (size_t)cta * 8 * S, 32768, bars + BAR_FULLB + 8 * ST_H, pol);
                unsigned kv_ready;
                asm volatile("ld.acquire.gpu.global.u32 %0, [%1];" : "=r"(kv_ready) : "l"(p.flags + FL_KV * FLAG_STRIDE) : "memory");
#pragma unroll 1
                for (int pass = 0; pass < 2; pass++) {
                    if ((pass == 0) == (kv_ready >= 4)) {
                        mbar_wait(bars + BAR_EMPTYB + 8 * ST_U, 1);
                        flag_wait(p.flags + FL_KV * FLAG_STRIDE, 4);
                        mbar_expect_tx(bars + BAR_FULLB + 8 * ST_U, 32768);
#pragma unroll 1
                        for (int ch = 0; ch < 8; ch++) bulk_g2s_h(sb + ST_U * B_STAGE + ch * U_PITCH, p.kvT + (size_t)(cta * 8 + ch) * S, 4096, bars + BAR_FULLB + 8 * ST_U, pol);
                    }
                    if (pass == 0) {
#pragma unroll 1
                        for (int c = 0; c < 4; c++) { mbar_wait(bars + BAR_EMPTYB + 8 * c, 0); mbar_arrive(bars + BAR_FULLB + 8 * c); }
                    }
                }
                flag_wait(p.flags + (FL_H + m2) * FLAG_STRIDE, 16);
                int i6 = 0; uint32_t rho = 0;
#pragma unroll 1
                for (int kb = 0; kb < 56; kb++) {
                    const int sg = (0x512034 >> (4 * i6)) & 15;
                    const uint32_t par = ((0x21u >> i6) & 1u) ^ rho;
                    const uint32_t full = bars + BAR_FULLB + 8 * sg, a = sb + sg * B_STAGE;
                    mbar_wait(bars + BAR_EMPTYB + 8 * sg, par ^ 1);
                    if (kb == 32) flag_wait(p.flags + (FL_H2 + m2) * FLAG_STRIDE, 16);
                    mbar_expect_tx(full, B_STAGE);
                    tma_2d_mc(a + rank * 8192, &p.tmH64, kb * 64, mrow2, full);
                    tma_3d(a + 16384, &p.tmWd, 0, kb * 64, n2 >> 6, full);
                    if (++i6 == 6) { i6 = 0; rho ^= 1; }
                }
                mbar_wait(bars + BAR_EMPTYB + 0, 0);
                mbar_expect_tx(bars + BAR_FULLB + 0, 32768);
                tma_2d(sb, &p.tmX128, n2, m2 * 128, bars + BAR_FULLB + 0);
                tma_2d(sb + 16384, &p.tmX128, n2 + 64, m2 * 128, bars + BAR_FULLB + 0);
                mbar_wait(bars + BAR_OPFULL, 0);
                unsigned old;
                asm volatile("atom.acq_rel.gpu.global.add.u32 %0, [%1], 1;" : "=r"(old) : "l"(p.flags + FL_DONE * FLAG_STRIDE) : "memory");
                if (old == NCTA - 1) {
#pragma unroll 1
                    for (int i = 0; i < FL_COUNT; i++) p.flags[i * FLAG_STRIDE] = 0;
                }
            } else {
                cluster_wait();
            }
        } else {
            cluster_wait();
            const int wt = tid - 32;
#pragma unroll 1
            for (int Ri = 0; Ri < 7; Ri++) {
                const int R = (Ri == 5) ? 6 : (Ri == 6) ? 5 : Ri;
                const uint32_t buf = (R == 4) ? sb + ST_ALT2 * B_STAGE : (R == 6) ? sb + ST_ALT * B_STAGE : sb + OFF_STG;
                mbar_wait_idle(bars + ((R == 4) ? BAR_ALT2FULL : (R == 6) ? BAR_ALTFULL : BAR_STGFULL), (R < 4) ? (R & 1) : 0);
#pragma unroll 1
                for (int i0 = wt; i0 < 1024; i0 += 2 * 96) {
                    const int i1 = i0 + 96;
                    const uint32_t a0 = buf + (i0 >> 9) * 16384 + (i0 & 511) * 16;
                    const uint32_t a1 = (i1 < 1024) ? buf + (i1 >> 9) * 16384 + (i1 & 511) * 16 : a0;
                    uint4 g0 = lds128(a0), u0 = lds128(a0 + 8192), g1 = lds128(a1), u1 = lds128(a1 + 8192);
                    g0.x = bf2_mul(silu_bf2(g0.x), u0.x); g0.y = bf2_mul(silu_bf2(g0.y), u0.y); g0.z = bf2_mul(silu_bf2(g0.z), u0.z); g0.w = bf2_mul(silu_bf2(g0.w), u0.w);
                    g1.x = bf2_mul(silu_bf2(g1.x), u1.x); g1.y = bf2_mul(silu_bf2(g1.y), u1.y); g1.z = bf2_mul(silu_bf2(g1.z), u1.z); g1.w = bf2_mul(silu_bf2(g1.w), u1.w);
                    sts128(a0, g0.x, g0.y, g0.z, g0.w);
                    if (i1 < 1024) sts128(a1, g1.x, g1.y, g1.z, g1.w);
                }
                fence_async_smem();
                bar_sync(4, 96);
                if (wt == 0) {
                    const int mm = (R < 6) ? m1 : m2;
                    const int col = (R < 6) ? (8 * (R >> 1) + nb1) * 128 + (R & 1) * 64 : nh * 128 + (int)rank * 64;
                    tma_store_2d(&p.tmH64, buf, col, mm * 128);
                    tma_store_2d(&p.tmH64, buf + 16384, col, mm * 128 + 64);
                    bulk_commit();
                    bulk_wait_read();
                    if (R != 4 && R != 6) mbar_arrive(bars + BAR_STGEMPTY);
                    else {
                        const uint32_t eb = bars + BAR_EMPTYB + 8 * ((R == 4) ? ST_ALT2 : ST_ALT);
                        mbar_arrive_cta(eb, 0); mbar_arrive_cta(eb, 0); mbar_arrive_cta(eb, 1); mbar_arrive_cta(eb, 1);
                    }
                    if (R == 1 || R == 3 || R >= 5) {
                        bulk_wait_all();
                        flag_add_after_bulk(p.flags + ((R < 4 ? FL_H : FL_H2) + mm) * FLAG_STRIDE);
                    }
                }
            }
            if (wt == 0) {
                mbar_wait(bars + BAR_FULLB + 8 * 3, 0); mbar_wait(bars + BAR_FULLB + 8 * 3, 1); mbar_wait(bars + BAR_FULLB + 8 * 3, 0);
                pf_2d(&p.tmX128, n2, m2 * 128); pf_2d(&p.tmX128, n2 + 64, m2 * 128);
                flag_wait(p.flags + (FL_Y + (n2 >> 7)) * FLAG_STRIDE, 128);
                mbar_expect_tx(bars + BAR_OPFULL, 32768);
                tma_2d(sb + OFF_STG, &p.tmY2T, 1984 - m2 * 128, n2, bars + BAR_OPFULL);
                tma_2d(sb + OFF_STG + 16384, &p.tmY2T, 1920 - m2 * 128, n2, bars + BAR_OPFULL);
            }
        }
        __syncwarp();
        cluster_sync();
    } else {
        asm volatile("setmaxnreg.inc.sync.aligned.u32 232;\n");
        const int cw = wg - 1;
        const int w = (tid >> 5) & 3;
        const int wtid = tid & 127;

        {
            const int rl = (cw * 4 + w) * 2 + (lane >> 4);
            const uint32_t src = sb + OFF_STG + rl * 2048 + (lane & 15) * 16;
            float s0 = 0.f, s1 = 0.f, s2 = 0.f, s3 = 0.f;
#pragma unroll
            for (int i = 0; i < 32; i += 2) { s0 += bf_lo(x[i]); s1 += bf_hi(x[i]); s2 += bf_lo(x[i + 1]); s3 += bf_hi(x[i + 1]); }
            float s = (s0 + s1) + (s2 + s3);
#pragma unroll
            for (int o = 8; o > 0; o >>= 1) s += __shfl_xor_sync(0xffffffffu, s, o);
            const float mu = s * (1.0f / D);
            s0 = s1 = s2 = s3 = 0.f;
#pragma unroll
            for (int i = 0; i < 32; i += 2) {
                const float a = bf_lo(x[i]) - mu, b = bf_hi(x[i]) - mu, c = bf_lo(x[i + 1]) - mu, d = bf_hi(x[i + 1]) - mu;
                s0 = fmaf(a, a, s0); s1 = fmaf(b, b, s1); s2 = fmaf(c, c, s2); s3 = fmaf(d, d, s3);
            }
            float v = (s0 + s1) + (s2 + s3);
#pragma unroll
            for (int o = 8; o > 0; o >>= 1) v += __shfl_xor_sync(0xffffffffu, v, o);
            const uint32_t mu2 = pack_bf2(mu, mu);
            const float vb = bf_lo(pack_bf2(v * (1.0f / D), 0.f));
            const float ve = bf_lo(pack_bf2(vb + 1e-5f, 0.f));
            const float sd = bf_lo(pack_bf2(sqrtf(ve), 0.f));
            const float inv = __frcp_rn(sd);
#pragma unroll
            for (int i = 0; i < 8; i++) {
                uint32_t oo[4];
#pragma unroll
                for (int e = 0; e < 4; e++) { const uint32_t dd = bf2_sub(x[4 * i + e], mu2); oo[e] = pack_bf2(bf_lo(dd) * inv, bf_hi(dd) * inv); }
                sts128(src + i * 256, oo[0], oo[1], oo[2], oo[3]);
            }
            if ((lane & 15) == 0) asm volatile("st.shared.v2.b32 [%0], {%1, %2};" :: "r"(bars + OFF_STAT + rl * 8), "r"(mu2), "r"(__float_as_uint(inv)) : "memory");
            fence_async_smem();
            __syncwarp();
            if (lane == 0) {
                bulk_s2g(p.xn + (size_t)(cta * 16 + (cw * 4 + w) * 2) * D, sb + OFF_STG + (cw * 4 + w) * 4096, 4096);
                bulk_s2g(p.stats + cta * 16 + (cw * 4 + w) * 2, bars + OFF_STAT + (cw * 4 + w) * 16, 16);
                bulk_commit();
                bulk_wait_all();
                flag_add_after_bulk(p.flags + (FL_XN + (cta >> 3)) * FLAG_STRIDE);
            }
            bar_sync(3, 256);
        }
        cluster_wait();

        const uint32_t lrow = w * 16 + (lane & 7) + ((lane >> 3) & 1) * 8;
        const uint32_t lrow7 = lane & 7;
        const uint32_t lgrp = lane >> 4;
        const uint32_t stg_lane = sb + OFF_STG + cw * 16384 + lrow * 128;
        const uint64_t descA = make_desc(sb + cw * 8192, 16, 1024);
        const uint64_t descB = make_desc(sb + 16384, 8192, 1024);

        int st = 0; uint32_t ph = 0;
        uint32_t pg[32], pu[32], qg[16], qu[16];
        {
            float acc[128];
            int prev = 0;
#pragma unroll 1
            for (int g = 0; g < 64; g++) {
                const int kb = g & 15;
                if (g < 48) {
                    const int sa = g & 3;
                    mbar_wait(bars + BAR_FULLA + 8 * sa, (g >> 2) & 1);
                    const uint64_t da = descA + sa * (A_STAGE >> 4), db = descB + sa * (A_STAGE >> 4);
                    wg_fence();
                    wgmma_256(acc, da, db, kb != 0);
#pragma unroll
                    for (int k = 1; k < 4; k++) wgmma_256(acc, da + k * 2, db + k * 128, 1);
                    wg_commit();
                } else {
                    mbar_wait(bars + BAR_FULLB + 8 * st, ph);
                    const uint64_t da = descA + st * (B_STAGE >> 4), db = descB + st * (B_STAGE >> 4);
                    wg_fence();
                    wgmma_128_lo(acc, da, db, kb != 0);
#pragma unroll
                    for (int k = 1; k < 4; k++) wgmma_128_lo(acc, da + k * 2, db + k * 128, 1);
                    wg_commit();
                }
                wg_wait<1>();
                if (kb > 0) {
                    if (wtid < 2) mbar_arrive_cta(bars + ((g > 48) ? BAR_EMPTYB + 8 * prev : BAR_EMPTYA + 8 * ((g - 1) & 3)), wtid);
                }
                if (g >= 48) { prev = st; if (++st == 6) { st = 0; ph ^= 1; } }
                if (g >= 16 && g < 48) {
                    const int pc = (kb < 4) ? kb : ((kb >= 9 && kb < 13) ? kb - 5 : -1);
                    if (pc >= 0) {
                        if (pc == 0 && g >= 32) mbar_wait(bars + BAR_STGEMPTY, 1);
                        if (pc == 4) mbar_wait(bars + BAR_STGEMPTY, 0);
                        stage_piece_dyn(pc, pg, pu, stg_lane, lrow7, lgrp);
                        if ((pc & 3) == 3) { __syncwarp(); if (lane == 0) mbar_arrive(bars + BAR_STGFULL); }
                    }
                }
                if (kb == 15 && g < 48) {
                    wg_wait<0>();
                    if (wtid < 2) mbar_arrive_cta(bars + BAR_EMPTYA + 24, wtid);
#pragma unroll
                    for (int i = 0; i < 32; i++) { pg[i] = pack_bf2(acc[2 * i], acc[2 * i + 1]); pu[i] = pack_bf2(acc[64 + 2 * i], acc[64 + 2 * i + 1]); }
                }
            }
            wg_wait<0>();
            if (wtid < 2) mbar_arrive_cta(bars + BAR_EMPTYB + 8 * prev, wtid);
#pragma unroll
            for (int i = 0; i < 16; i++) { qg[i] = pack_bf2(acc[2 * i], acc[2 * i + 1]); qu[i] = pack_bf2(acc[32 + 2 * i], acc[32 + 2 * i + 1]); }
        }
        mbar_wait(bars + BAR_FULLB + 8 * ST_ALT2, 1);
        {
            const uint32_t alt_lane = sb + ST_ALT2 * B_STAGE + cw * 16384 + lrow * 128;
            stage_piece<0>(pg, pu, alt_lane, lrow7, lgrp); stage_piece<1>(pg, pu, alt_lane, lrow7, lgrp);
            stage_piece<2>(pg, pu, alt_lane, lrow7, lgrp); stage_piece<3>(pg, pu, alt_lane, lrow7, lgrp);
            __syncwarp(); if (lane == 0) mbar_arrive(bars + BAR_ALT2FULL);
        }
        mbar_wait(bars + BAR_STGEMPTY, 1);
        stage_piece<4>(pg, pu, stg_lane, lrow7, lgrp); stage_piece<5>(pg, pu, stg_lane, lrow7, lgrp);
        stage_piece<6>(pg, pu, stg_lane, lrow7, lgrp); stage_piece<7>(pg, pu, stg_lane, lrow7, lgrp);
        __syncwarp(); if (lane == 0) mbar_arrive(bars + BAR_STGFULL);
        mbar_wait(bars + BAR_FULLB + 8 * ST_ALT, 1);
        {
            const uint32_t alt_lane = sb + ST_ALT * B_STAGE + cw * 16384 + lrow * 128;
#pragma unroll
            for (int i = 0; i < 4; i++) {
                const uint32_t addr = alt_lane + (((2 * i + lgrp) ^ lrow7) << 4);
                stsm_x4(addr, qg[4 * i], qg[4 * i + 1], qg[4 * i + 2], qg[4 * i + 3]);
                stsm_x4(addr + 8192, qu[4 * i], qu[4 * i + 1], qu[4 * i + 2], qu[4 * i + 3]);
            }
            __syncwarp(); if (lane == 0) mbar_arrive(bars + BAR_ALTFULL);
        }
        {
            const int r = lane >> 2, c4 = lane & 3;
            mbar_wait(bars + BAR_FULLB + 8 * ST_H, 0);
            mbar_wait(bars + BAR_FULLB + 8 * ST_C0, 1);
            mbar_wait(bars + BAR_FULLB + 8 * ST_C1, 1);
            {
                const uint32_t sH = sb + ST_H * B_STAGE + (cw * 4 + w) * 4096;
                const uint32_t sA = sb + (w >> 1) * B_STAGE + ((w & 1) * 2 + cw) * 8192, sB = sA + 4096;
                uint4 hv[8]; uint32_t hp[8];
#pragma unroll
                for (int i = 0; i < 8; i++) {
                    const int Q = i * 32 + lane;
                    hv[i] = lds128(sH + (255 - Q) * 16);
                    hp[i] = lds32(sH + (254 - Q) * 16 + 12);
                }
                if (lane == 31) hp[7] = 0;
                const uint32_t qs = (uint32_t)(lane ^ ((lane >> 3) & 3)) * 16;
#pragma unroll
                for (int i = 0; i < 8; i++) {
                    const uint4 a = hv[i];
                    const uint32_t prev = hp[i];
                    sts128(sA + i * 512 + qs, __byte_perm(a.w, 0, 0x1032), __byte_perm(a.z, 0, 0x1032), __byte_perm(a.y, 0, 0x1032), __byte_perm(a.x, 0, 0x1032));
                    sts128(sB + i * 512 + (qs ^ 64), __byte_perm(a.w, a.z, 0x7610), __byte_perm(a.z, a.y, 0x7610), __byte_perm(a.y, a.x, 0x7610), __byte_perm(a.x, prev, 0x7610));
                }
            }
            mbar_wait(bars + BAR_FULLB + 8 * ST_U, 0);
            if (lane < 8) sts128(sb + ST_U * B_STAGE + (cw * 4 + w) * U_PITCH + 4096 + lane * 16, 0, 0, 0, 0);
            fence_async_smem();
            bar_sync(1 + cw, 128);
            if (wtid < 2) mbar_arrive_cta(bars + BAR_EMPTYB + 8 * ST_H, wtid);
            if (cw == 1) bar_arrive(5, 256);
            const uint32_t podd = r & 1, b0 = (r >> 1) & 1, b1 = r >> 2;
            const int w0 = 1023 - w + c4 - 32 * (r >> 1);
            const uint32_t cpy = podd ? 0u : 4096u, xb = podd ? 0u : 16u;
            const int y0 = 2 * w + (int)podd - 2 * c4;
            const uint32_t mask0 = (r >> 1) ? 0xFFFFFFFFu : ((y0 >= 0 ? 0x0000FFFFu : 0u) | (y0 >= 1 ? 0xFFFF0000u : 0u));
            uint32_t a[16][4];
            {
                uint32_t hx[8];
                conv_frag_addr(hx, sb + cw * 8192 + cpy, w0, xb);
                conv_load_a<0>(a, hx);
                a[0][0] &= mask0;
            }
            const uint2 dq = __ldg(reinterpret_cast<const uint2*>(p.ssm_D + cta * 8 + cw * 4));
            auto conv_finish = [&](int cp) {
                const uint32_t sA = sb + (cp >> 1) * B_STAGE + ((cp & 1) * 2 + cw) * 8192;
                const uint32_t sU = sb + ST_U * B_STAGE + (cw * 4 + cp) * U_PITCH;
                const uint32_t dw = (cp & 2) ? dq.y : dq.x;
                const uint32_t d2 = __byte_perm(dw, 0, (cp & 1) ? 0x3232 : 0x1010);
#pragma unroll
                for (int i = 0; i < 2; i++) {
                    const uint32_t beta = 64 * w + 32 * i + lane;
                    const uint4 kv = lds128(sU + beta * 16);
                    const uint32_t y0w = lds32_o<0>(sA + beta * 4), y1w = lds32_o<1024>(sA + beta * 4), y2w = lds32_o<2048>(sA + beta * 4), y3w = lds32_o<3072>(sA + beta * 4);
                    sts128(sU + beta * 16, bf2_add(y0w, bf2_mul(kv.x, d2)), bf2_add(y1w, bf2_mul(kv.y, d2)), bf2_add(y2w, bf2_mul(kv.z, d2)), bf2_add(y3w, bf2_mul(kv.w, d2)));
                }
            };
            auto conv_store = [&](int cp) {
                const int ch = cw * 4 + cp;
                fence_async_smem();
                __syncwarp();
                if (lane == 0) { bulk_s2g(p.y2T + (size_t)(cta * 8 + ch) * S + w * 512, sb + ST_U * B_STAGE + ch * U_PITCH + w * 1024, 1024); bulk_commit(); }
                if (cp & 1) { bar_sync(1 + cw, 128); if (wtid < 2) mbar_arrive_cta(bars + BAR_EMPTYB + 8 * (cp >> 1), wtid); }
            };
#pragma unroll 1
            for (int ci = 0; ci < 4; ci++) {
                const int k = 2 * ci + cw;
                float acc[128];
                bar_sync(5 + cw, 256);
                wg_fence();
                conv_issue<0>(acc, a, make_desc_noswz(sb + ST_U * B_STAGE + (cw * 4 + ci) * U_PITCH, 16, 128));
                wg_commit();
                if (k < 7) bar_arrive(5 + (cw ^ 1), 256);
                if (ci > 0) conv_finish(ci - 1);
                wg_wait<0>();
                if (ci > 0) conv_store(ci - 1);
                float f[16];
                {
                    float wv[34];
#pragma unroll
                    for (int i = 0; i < 16; i++) {
#pragma unroll
                        for (int jj = 0; jj < 2; jj++) {
                            const float ve = acc[8 * i + jj] + ((2 * i + 4 < 32) ? acc[4 * (2 * i + 4) + 2 + jj] : 0.f);
                            const float vo = acc[8 * i + 4 + jj] + ((2 * i + 5 < 32) ? acc[4 * (2 * i + 5) + 2 + jj] : 0.f);
                            const float vn = (i < 15) ? acc[8 * i + 8 + jj] + ((2 * i + 6 < 32) ? acc[4 * (2 * i + 6) + 2 + jj] : 0.f) : 0.f;
                            wv[2 * i + jj] = (b0 ? vn : ve) + __shfl_xor_sync(0xffffffffu, vo, 8);
                        }
                    }
                    wv[32] = wv[33] = 0.f;
#pragma unroll
                    for (int kk = 0; kk < 8; kk++)
#pragma unroll
                        for (int jj = 0; jj < 2; jj++)
                            f[2 * kk + jj] = (b1 ? wv[4 * kk + 4 + jj] : wv[4 * kk + jj]) + __shfl_xor_sync(0xffffffffu, wv[4 * kk + 2 + jj], 16);
                }
                {
                    const uint32_t sA = sb + (ci >> 1) * B_STAGE + ((ci & 1) * 2 + cw) * 8192;
#pragma unroll
                    for (int kk = 0; kk < 8; kk++) {
                        const float keep = podd ? f[2 * kk + 1] : f[2 * kk];
                        const float recv = __shfl_xor_sync(0xffffffffu, podd ? f[2 * kk] : f[2 * kk + 1], 4);
                        const uint32_t yw = pack_bf2(podd ? recv : keep, podd ? keep : recv);
                        asm volatile("st.shared.b32 [%0], %1;" :: "r"(sA + w * 1024 + (32 * kk + 8 * (r >> 1) + 2 * c4 + podd) * 4), "r"(yw) : "memory");
                    }
                }
                if (ci < 3) {
                    uint32_t hx[8];
                    conv_frag_addr(hx, sb + ((ci + 1) >> 1) * B_STAGE + (((ci + 1) & 1) * 2 + cw) * 8192 + cpy, w0, xb);
                    conv_load_a<0>(a, hx);
                    a[0][0] &= mask0;
                }
            }
            bar_sync(1 + cw, 128);
            conv_finish(3);
            conv_store(3);
            if (lane == 0) bulk_wait_read();
            bar_sync(1 + cw, 128);
            if (wtid < 2) mbar_arrive_cta(bars + BAR_EMPTYB + 8 * ST_U, wtid);
        }
        {
            float acc[64];
            const int srow = m2 * 128 + cw * 64 + w * 16 + (lane >> 2);
            const uint2 st0 = __ldcg(p.stats + srow), st1 = __ldcg(p.stats + srow + 8);
            int i6 = 0, prev = 0; uint32_t rho = 0;
#pragma unroll 1
            for (int kb = 0; kb < 56; kb++) {
                const int sg = (0x512034 >> (4 * i6)) & 15;
                mbar_wait(bars + BAR_FULLB + 8 * sg, ((0x21u >> i6) & 1u) ^ rho);
                const uint64_t da = descA + sg * (B_STAGE >> 4), db = descB + sg * (B_STAGE >> 4);
                wg_fence();
                wgmma_128(acc, da, db, kb != 0);
#pragma unroll
                for (int k = 1; k < 4; k++) wgmma_128(acc, da + k * 2, db + k * 128, 1);
                wg_commit();
                                if (kb == 8 && lane == 0) { bulk_wait_all(); flag_add_after_bulk(p.flags + (FL_Y + (cta >> 4)) * FLAG_STRIDE); }
                wg_wait<1>();
                if (kb > 0 && wtid < 2) mbar_arrive_cta(bars + BAR_EMPTYB + 8 * prev, wtid);
                prev = sg;
                if (++i6 == 6) { i6 = 0; rho ^= 1; }
            }
            mbar_wait(bars + BAR_OPFULL, 0);
            wg_wait<0>();
            mbar_wait(bars + BAR_FULLB + 0, 1);
            const float inv0 = __uint_as_float(st0.y), inv1 = __uint_as_float(st1.y);
            const uint32_t ycol = sb + OFF_STG + cw * 16384 + (((7 - 2 * w - ((lane >> 3) & 1)) ^ lrow7) << 4) + lrow7 * 128;
            const uint32_t xrow = sb + (cw * 64 + lrow) * 128;
#pragma unroll 1
            for (int g2 = 0; g2 < 2; g2++) {
#pragma unroll
                for (int hh = 0; hh < 4; hh++) {
                    const uint32_t grp = hh * 2 + lgrp;
                    const uint32_t xa = xrow + g2 * 16384 + ((grp ^ lrow7) << 4);
                    uint32_t x[4], y[4], o[4];
                    ldsm_x4(xa, x[0], x[1], x[2], x[3]);
                    ldsm_x4_t(ycol + (g2 * 8 + grp) * 1024, y[0], y[1], y[2], y[3]);
#pragma unroll
                    for (int i = 0; i < 4; i++) {
                        const uint32_t dd = bf2_sub(x[i], (i & 1) ? st1.x : st0.x);
                        const float iv = (i & 1) ? inv1 : inv0;
                        const uint32_t xn = pack_bf2(bf_lo(dd) * iv, bf_hi(dd) * iv);
                        o[i] = bf2_add(x[i], bf2_mul(bf2_mul(xn, y[i]), silu_bf2(pack_bf2(acc[8 * hh + 2 * i], acc[8 * hh + 2 * i + 1]))));
                    }
                    stsm_x4(xa, o[0], o[1], o[2], o[3]);
                }
#pragma unroll
                for (int i = 0; i < 32; i++) acc[i] = acc[i + 32];
                fence_async_smem();
                bar_sync(1 + cw, 128);
                if (wtid == 0) { tma_store_2d(&p.tmOut64, sb + g2 * 16384 + cw * 8192, n2 + g2 * 64, m2 * 128 + cw * 64); bulk_commit(); }
            }
            if (wtid == 0) bulk_wait_read();
        }
        cluster_sync();
    }
}

typedef CUresult (*EncodeTiledFn)(CUtensorMap*, CUtensorMapDataType, cuuint32_t, void*, const cuuint64_t*, const cuuint64_t*,
                                  const cuuint32_t*, const cuuint32_t*, CUtensorMapInterleave, CUtensorMapSwizzle,
                                  CUtensorMapL2promotion, CUtensorMapFloatOOBfill);

static void make_map(EncodeTiledFn enc, CUtensorMap* m, const void* ptr, int rank, const uint64_t* dims, const uint64_t* strides, const uint32_t* box,
                     CUtensorMapSwizzle swz = CU_TENSOR_MAP_SWIZZLE_128B) {
    cuuint64_t d[3], s[2];
    cuuint32_t b[3], es[3] = {1, 1, 1};
    for (int i = 0; i < rank; i++) { d[i] = dims[i]; b[i] = box[i]; }
    for (int i = 0; i + 1 < rank; i++) s[i] = strides[i];
    CUresult r = enc(m, CU_TENSOR_MAP_DATA_TYPE_BFLOAT16, rank, const_cast<void*>(ptr), d, s, b, es, CU_TENSOR_MAP_INTERLEAVE_NONE,
                     swz, CU_TENSOR_MAP_L2_PROMOTION_L2_128B, CU_TENSOR_MAP_FLOAT_OOB_FILL_NONE);
    if (r != CUDA_SUCCESS) fprintf(stderr, "cuTensorMapEncodeTiled failed: %d\n", (int)r);
}
static void map2d(EncodeTiledFn enc, CUtensorMap* m, const void* ptr, uint64_t cols, uint64_t rows, uint32_t box_rows) {
    const uint64_t d[2] = {cols, rows}, s[1] = {cols * 2};
    const uint32_t b[2] = {64, box_rows};
    make_map(enc, m, ptr, 2, d, s, b);
}
static void map3d(EncodeTiledFn enc, CUtensorMap* m, const void* ptr, uint64_t cols, uint64_t rows, uint32_t groups) {
    const uint64_t d[3] = {64, rows, cols / 64}, s[2] = {cols * 2, 128};
    const uint32_t b[3] = {64, 64, groups};
    make_map(enc, m, ptr, 3, d, s, b);
}

}

extern "C" void kernel_launch(void* const* d_in, const int* in_sizes, int n_in, void* d_out, int out_size) {
    using namespace h3;
    (void)in_sizes; (void)n_in; (void)out_size;
    static EncodeTiledFn enc = nullptr;
    static void *xn, *kvT, *hbuf, *y2T, *flags, *stats;
    if (!enc) {
        void* fn = nullptr;
        cudaDriverEntryPointQueryResult qr;
        cudaGetDriverEntryPoint("cuTensorMapEncodeTiled", &fn, cudaEnableDefault, &qr);
        enc = (EncodeTiledFn)fn;
        cudaGetSymbolAddress(&xn, g_xn);
        cudaGetSymbolAddress(&kvT, g_kvT);
        cudaGetSymbolAddress(&hbuf, g_h);
        cudaGetSymbolAddress(&y2T, g_y2T);
        cudaGetSymbolAddress(&flags, g_flags);
        cudaGetSymbolAddress(&stats, g_stats);
        cudaFuncSetAttribute(h3_kernel, cudaFuncAttributeMaxDynamicSharedMemorySize, SMEM_BYTES);
    }
    Params p;
    const bf16* q = (const bf16*)d_in[0];
    p.q = q; p.k = (const bf16*)d_in[1]; p.v = (const bf16*)d_in[2];
    p.shift_k = (const bf16*)d_in[3]; p.ssm_k = (const bf16*)d_in[4]; p.ssm_D = (const bf16*)d_in[5];
    const bf16* wg = (const bf16*)d_in[7];
    const bf16* wu = (const bf16*)d_in[8];
    const bf16* wd = (const bf16*)d_in[9];
    p.xn = (bf16*)xn; p.kvT = (bf16*)kvT; p.y2T = (bf16*)y2T; p.flags = (unsigned*)flags; p.stats = (uint2*)stats;
    map2d(enc, &p.tmXn128, xn, D, S, 128);
    map2d(enc, &p.tmXn64, xn, D, S, 64);
    map3d(enc, &p.tmWg2, wg, F, D, 2);
    map3d(enc, &p.tmWu2, wu, F, D, 2);
    map3d(enc, &p.tmWg1, wg, F, D, 1);
    map3d(enc, &p.tmWu1, wu, F, D, 1);
    map2d(enc, &p.tmH64, hbuf, F, S, 64);
    map3d(enc, &p.tmWd, wd, D, F, 2);
    map2d(enc, &p.tmX128, q, D, S, 128);
    map2d(enc, &p.tmY2T, y2T, S, D, 128);
    map2d(enc, &p.tmOut64, d_out, D, S, 64);
    {
        const uint64_t d[2] = {D, S}, st[1] = {D * 2};
        const uint32_t bk[2] = {128, 67}, bv[2] = {128, 64};
        make_map(enc, &p.tmK, p.k, 2, d, st, bk, CU_TENSOR_MAP_SWIZZLE_NONE);
        make_map(enc, &p.tmV, p.v, 2, d, st, bv, CU_TENSOR_MAP_SWIZZLE_NONE);
    }
    map2d(enc, &p.tmKvT, kvT, S, D, 128);

    cudaLaunchConfig_t cfg = {};
    cfg.gridDim = dim3(NCTA + 4);
    cfg.blockDim = dim3(384);
    cfg.dynamicSmemBytes = SMEM_BYTES;
    cfg.stream = cudaStreamPerThread;
    cudaLaunchAttribute at[1];
    at[0].id = cudaLaunchAttributeClusterDimension;
    at[0].val.clusterDim.x = 2; at[0].val.clusterDim.y = 1; at[0].val.clusterDim.z = 1;
    cfg.attrs = at; cfg.numAttrs = 1;
    cudaLaunchKernelEx(&cfg, h3_kernel, p);
}
```

```cpp
#include <cuda_runtime.h>
#include <cuda_bf16.h>
#include <cuda.h>
#include <stdint.h>
#include <stdio.h>

namespace h3 {

typedef __nv_bfloat16 bf16;

constexpr int S = 2048;
constexpr int D = 1024;
constexpr int F = 3584;
constexpr int NCTA = 128;

__device__ __align__(1024) bf16 g_xn[S * D];
__device__ __align__(1024) bf16 g_kvT[D * S];
__device__ __align__(1024) bf16 g_h[S * F];
__device__ __align__(1024) bf16 g_y2T[D * S];
__device__ __align__(1024) uint2 g_stats[S];
constexpr int FLAG_STRIDE = 32;
constexpr int FL_XN = 0, FL_H = 16, FL_Y = 32, FL_KV = 40, FL_DONE = 41, FL_H2 = 42, FL_COUNT = 58;
__device__ __align__(1024) unsigned g_flags[FL_COUNT * FLAG_STRIDE];

struct alignas(64) Params {
    CUtensorMap tmXn128;
    CUtensorMap tmXn64;
    CUtensorMap tmWg2;
    CUtensorMap tmWu2;
    CUtensorMap tmWg1;
    CUtensorMap tmWu1;
    CUtensorMap tmH64;
    CUtensorMap tmWd;
    CUtensorMap tmX128;
    CUtensorMap tmY2T;
    CUtensorMap tmOut64;
    CUtensorMap tmK;
    CUtensorMap tmV;
    CUtensorMap tmKvT;
    const bf16* q; const bf16* k; const bf16* v; const bf16* shift_k; const bf16* ssm_k; const bf16* ssm_D;
    bf16* xn; bf16* kvT; bf16* y2T; uint2* stats;
    unsigned* flags;
};

constexpr uint32_t RING_BYTES = 196608;
constexpr uint32_t A_STAGE = 49152, B_STAGE = 32768;
constexpr uint32_t OFF_STG = RING_BYTES + 1024;
constexpr uint32_t OFF_BAR = OFF_STG + 32768;
constexpr uint32_t BAR_FULLA = 0, BAR_EMPTYA = 32, BAR_FULLB = 96, BAR_EMPTYB = 144,
                   BAR_STGFULL = 200, BAR_STGEMPTY = 208, BAR_ALTFULL = 216, BAR_OPFULL = 232,
                   BAR_ALT2FULL = 240, OFF_STAT = 256;
constexpr uint32_t SMEM_BYTES = OFF_BAR + 512 + 1024;

constexpr int ST_H = 4, ST_U = 5, ST_C0 = 0, ST_C1 = 1, ST_ALT = 2, ST_ALT2 = 3;
constexpr uint32_t U_PITCH = 4096 + 128;

__device__ __forceinline__ uint32_t smem_u32(const void* p) { return (uint32_t)__cvta_generic_to_shared(p); }
__device__ __forceinline__ uint64_t make_desc(uint32_t addr, uint32_t lbo, uint32_t sbo) {
    uint64_t d = (uint64_t)((addr & 0x3FFFF) >> 4);
    d |= (uint64_t)((lbo & 0x3FFFF) >> 4) << 16;
    d |= (uint64_t)((sbo & 0x3FFFF) >> 4) << 32;
    d |= (uint64_t)1 << 62;
    return d;
}
__device__ __forceinline__ uint64_t make_desc_noswz(uint32_t addr, uint32_t lbo, uint32_t sbo) {
    return (uint64_t)((addr & 0x3FFFF) >> 4) | ((uint64_t)(lbo >> 4) << 16) | ((uint64_t)(sbo >> 4) << 32);
}
constexpr uint32_t WAIT_LIMIT = 1u << 27;
__device__ __forceinline__ void mbar_init(uint32_t bar, uint32_t count) { asm volatile("mbarrier.init.shared::cta.b64 [%0], %1;" :: "r"(bar), "r"(count) : "memory"); }
__device__ __forceinline__ void mbar_expect_tx(uint32_t bar, uint32_t bytes) { asm volatile("mbarrier.arrive.expect_tx.shared::cta.b64 _, [%0], %1;" :: "r"(bar), "r"(bytes) : "memory"); }
__device__ __forceinline__ void mbar_arrive(uint32_t bar) { asm volatile("mbarrier.arrive.shared::cta.b64 _, [%0];" :: "r"(bar) : "memory"); }
__device__ __forceinline__ void mbar_arrive_cta(uint32_t bar, uint32_t cta) {
    asm volatile("{\n.reg .b32 ra;\nmapa.shared::cluster.u32 ra, %0, %1;\nmbarrier.arrive.shared::cluster.b64 _, [ra];\n}" :: "r"(bar), "r"(cta) : "memory");
}
__device__ __forceinline__ uint32_t mbar_try(uint32_t bar, uint32_t parity) {
    uint32_t ok;
    asm volatile("{\n.reg .pred p;\nmbarrier.try_wait.parity.shared::cta.b64 p, [%1], %2;\nselp.u32 %0, 1, 0, p;\n}" : "=r"(ok) : "r"(bar), "r"(parity) : "memory");
    return ok;
}
__device__ __forceinline__ void mbar_wait(uint32_t bar, uint32_t parity) {
    if (!mbar_try(bar, parity)) {
        const uint32_t t0 = (uint32_t)clock();
        while (!mbar_try(bar, parity) && (uint32_t)clock() - t0 < WAIT_LIMIT) {}
    }
}
__device__ __forceinline__ void mbar_wait_idle(uint32_t bar, uint32_t parity) {
    const uint32_t t0 = (uint32_t)clock();
    while (!mbar_try(bar, parity) && (uint32_t)clock() - t0 < WAIT_LIMIT) {
        __nanosleep(256);
    }
}
__device__ __forceinline__ void flag_wait(const unsigned* f, unsigned target) {
    const uint32_t t0 = (uint32_t)clock();
    unsigned v;
    do {
        asm volatile("ld.acquire.gpu.global.u32 %0, [%1];" : "=r"(v) : "l"(f) : "memory");
    } while (v < target && (uint32_t)clock() - t0 < WAIT_LIMIT);
}
__device__ __forceinline__ void flag_add_after_bulk(unsigned* f) {
    asm volatile("red.relaxed.gpu.global.add.u32 [%0], 1;" :: "l"(f) : "memory");
}
__device__ __forceinline__ void cluster_arrive() { asm volatile("barrier.cluster.arrive.relaxed;" ::: "memory"); }
__device__ __forceinline__ void cluster_wait() { asm volatile("barrier.cluster.wait.acquire;" ::: "memory"); }
__device__ __forceinline__ void tma_2d(uint32_t dst, const CUtensorMap* m, int c0, int c1, uint32_t bar) {
    asm volatile("cp.async.bulk.tensor.2d.shared::cluster.global.mbarrier::complete_tx::bytes [%0], [%1, {%3, %4}], [%2];"
        :: "r"(dst), "l"(m), "r"(bar), "r"(c0), "r"(c1) : "memory");
}
__device__ __forceinline__ void tma_2d_mc(uint32_t dst, const CUtensorMap* m, int c0, int c1, uint32_t bar) {
    asm volatile("cp.async.bulk.tensor.2d.shared::cluster.global.mbarrier::complete_tx::bytes.multicast::cluster [%0], [%1, {%3, %4}], [%2], %5;"
        :: "r"(dst), "l"(m), "r"(bar), "r"(c0), "r"(c1), "h"((uint16_t)3) : "memory");
}
__device__ __forceinline__ void tma_3d(uint32_t dst, const CUtensorMap* m, int c0, int c1, int c2, uint32_t bar) {
    asm volatile("cp.async.bulk.tensor.3d.shared::cluster.global.mbarrier::complete_tx::bytes [%0], [%1, {%3, %4, %5}], [%2];"
        :: "r"(dst), "l"(m), "r"(bar), "r"(c0), "r"(c1), "r"(c2) : "memory");
}
__device__ __forceinline__ uint64_t policy_evict_first() {
    uint64_t pol; asm volatile("createpolicy.fractional.L2::evict_first.b64 %0, 1.0;" : "=l"(pol)); return pol;
}
__device__ __forceinline__ void tma_3d_h(uint32_t dst, const CUtensorMap* m, int c0, int c1, int c2, uint32_t bar, uint64_t pol) {
    asm volatile("cp.async.bulk.tensor.3d.shared::cluster.global.mbarrier::complete_tx::bytes.L2::cache_hint [%0], [%1, {%3, %4, %5}], [%2], %6;"
        :: "r"(dst), "l"(m), "r"(bar), "r"(c0), "r"(c1), "r"(c2), "l"(pol) : "memory");
}
__device__ __forceinline__ void tma_2d_h(uint32_t dst, const CUtensorMap* m, int c0, int c1, uint32_t bar, uint64_t pol) {
    asm volatile("cp.async.bulk.tensor.2d.shared::cluster.global.mbarrier::complete_tx::bytes.L2::cache_hint [%0], [%1, {%3, %4}], [%2], %5;"
        :: "r"(dst), "l"(m), "r"(bar), "r"(c0), "r"(c1), "l"(pol) : "memory");
}
__device__ __forceinline__ void pf_bulk_h(const void* src, uint32_t bytes, uint64_t pol) {
    asm volatile("cp.async.bulk.prefetch.L2.global.L2::cache_hint [%0], %1, %2;" :: "l"(src), "r"(bytes), "l"(pol) : "memory");
}
__device__ __forceinline__ void tma_3d_mc_h(uint32_t dst, const CUtensorMap* m, int c0, int c1, int c2, uint32_t bar, uint64_t pol) {
    asm volatile("cp.async.bulk.tensor.3d.shared::cluster.global.mbarrier::complete_tx::bytes.multicast::cluster.L2::cache_hint [%0], [%1, {%3, %4, %5}], [%2], %6, %7;"
        :: "r"(dst), "l"(m), "r"(bar), "r"(c0), "r"(c1), "r"(c2), "h"((uint16_t)3), "l"(pol) : "memory");
}
__device__ __forceinline__ void bulk_g2s_h(uint32_t dst, const void* src, uint32_t bytes, uint32_t bar, uint64_t pol) {
    asm volatile("cp.async.bulk.shared::cluster.global.mbarrier::complete_tx::bytes.L2::cache_hint [%0], [%1], %2, [%3], %4;"
        :: "r"(dst), "l"(src), "r"(bytes), "r"(bar), "l"(pol) : "memory");
}
__device__ __forceinline__ void bulk_s2g(void* dst, uint32_t src, uint32_t bytes) {
    asm volatile("cp.async.bulk.global.shared::cta.bulk_group [%0], [%1], %2;" :: "l"(dst), "r"(src), "r"(bytes) : "memory");
}
__device__ __forceinline__ void tma_store_2d(const CUtensorMap* m, uint32_t src, int c0, int c1) {
    asm volatile("cp.async.bulk.tensor.2d.global.shared::cta.bulk_group [%0, {%2, %3}], [%1];"
        :: "l"(m), "r"(src), "r"(c0), "r"(c1) : "memory");
}
__device__ __forceinline__ void pf_2d(const CUtensorMap* m, int c0, int c1) {
    asm volatile("cp.async.bulk.prefetch.tensor.2d.L2.global.tile [%0, {%1, %2}];" :: "l"(m), "r"(c0), "r"(c1) : "memory");
}
__device__ __forceinline__ void pf_bulk(const void* src, uint32_t bytes) {
    asm volatile("cp.async.bulk.prefetch.L2.global [%0], %1;" :: "l"(src), "r"(bytes) : "memory");
}
__device__ __forceinline__ void bulk_commit() { asm volatile("cp.async.bulk.commit_group;" ::: "memory"); }
__device__ __forceinline__ void bulk_wait_read() { asm volatile("cp.async.bulk.wait_group.read 0;" ::: "memory"); }
__device__ __forceinline__ void bulk_wait_all() { asm volatile("cp.async.bulk.wait_group 0;" ::: "memory"); }
__device__ __forceinline__ void fence_async_smem() { asm volatile("fence.proxy.async.shared::cta;" ::: "memory"); }
__device__ __forceinline__ void bar_sync(int id, int n) { asm volatile("bar.sync %0, %1;" :: "r"(id), "r"(n) : "memory"); }
__device__ __forceinline__ void bar_arrive(int id, int n) { asm volatile("bar.arrive %0, %1;" :: "r"(id), "r"(n) : "memory"); }
__device__ __forceinline__ void cluster_wait_end() { asm volatile("barrier.cluster.wait;" ::: "memory"); }
__device__ __forceinline__ void cluster_sync() {
    asm volatile("barrier.cluster.arrive.relaxed.aligned;" ::: "memory");
    asm volatile("barrier.cluster.wait.aligned;" ::: "memory");
}
__device__ __forceinline__ void wg_fence() { asm volatile("wgmma.fence.sync.aligned;" ::: "memory"); }
__device__ __forceinline__ void wg_commit() { asm volatile("wgmma.commit_group.sync.aligned;" ::: "memory"); }
template <int N> __device__ __forceinline__ void wg_wait() { asm volatile("wgmma.wait_group.sync.aligned %0;" :: "n"(N) : "memory"); }

#define H3_R4(b)  "+f"(d[b+0]), "+f"(d[b+1]), "+f"(d[b+2]), "+f"(d[b+3])
#define H3_R8(b)  H3_R4(b), H3_R4(b+4)
#define H3_R16(b) H3_R8(b), H3_R8(b+8)
#define H3_R32(b) H3_R16(b), H3_R16(b+16)
#define H3_R64(b) H3_R32(b), H3_R32(b+32)

__device__ __forceinline__ void wgmma_256(float (&d)[128], uint64_t a, uint64_t b, int scale_d) {
    asm volatile("{\n.reg .pred p;\nsetp.ne.b32 p, %130, 0;\n"
    "wgmma.mma_async.sync.aligned.m64n256k16.f32.bf16.bf16 "
    "{%0,%1,%2,%3,%4,%5,%6,%7,%8,%9,%10,%11,%12,%13,%14,%15,"
    "%16,%17,%18,%19,%20,%21,%22,%23,%24,%25,%26,%27,%28,%29,%30,%31,"
    "%32,%33,%34,%35,%36,%37,%38,%39,%40,%41,%42,%43,%44,%45,%46,%47,"
    "%48,%49,%50,%51,%52,%53,%54,%55,%56,%57,%58,%59,%60,%61,%62,%63,"
    "%64,%65,%66,%67,%68,%69,%70,%71,%72,%73,%74,%75,%76,%77,%78,%79,"
    "%80,%81,%82,%83,%84,%85,%86,%87,%88,%89,%90,%91,%92,%93,%94,%95,"
    "%96,%97,%98,%99,%100,%101,%102,%103,%104,%105,%106,%107,%108,%109,%110,%111,"
    "%112,%113,%114,%115,%116,%117,%118,%119,%120,%121,%122,%123,%124,%125,%126,%127},"
    "%128, %129, p, 1, 1, 0, 1;\n}\n"
    : H3_R64(0), H3_R64(64)
    : "l"(a), "l"(b), "r"(scale_d));
}
__device__ __forceinline__ void wgmma_128(float (&d)[64], uint64_t a, uint64_t b, int scale_d) {
    asm volatile("{\n.reg .pred p;\nsetp.ne.b32 p, %66, 0;\n"
    "wgmma.mma_async.sync.aligned.m64n128k16.f32.bf16.bf16 "
    "{%0,%1,%2,%3,%4,%5,%6,%7,%8,%9,%10,%11,%12,%13,%14,%15,"
    "%16,%17,%18,%19,%20,%21,%22,%23,%24,%25,%26,%27,%28,%29,%30,%31,"
    "%32,%33,%34,%35,%36,%37,%38,%39,%40,%41,%42,%43,%44,%45,%46,%47,"
    "%48,%49,%50,%51,%52,%53,%54,%55,%56,%57,%58,%59,%60,%61,%62,%63},"
    "%64, %65, p, 1, 1, 0, 1;\n}\n"
    : H3_R64(0)
    : "l"(a), "l"(b), "r"(scale_d));
}
__device__ __forceinline__ void ldsm_x4(uint32_t addr, uint32_t& r0, uint32_t& r1, uint32_t& r2, uint32_t& r3) {
    asm volatile("ldmatrix.sync.aligned.m8n8.x4.shared.b16 {%0,%1,%2,%3}, [%4];" : "=r"(r0), "=r"(r1), "=r"(r2), "=r"(r3) : "r"(addr) : "memory");
}
__device__ __forceinline__ void ldsm_x4_t(uint32_t addr, uint32_t& r0, uint32_t& r1, uint32_t& r2, uint32_t& r3) {
    asm volatile("ldmatrix.sync.aligned.m8n8.x4.trans.shared.b16 {%0,%1,%2,%3}, [%4];" : "=r"(r0), "=r"(r1), "=r"(r2), "=r"(r3) : "r"(addr) : "memory");
}
__device__ __forceinline__ void stsm_x4(uint32_t addr, uint32_t r0, uint32_t r1, uint32_t r2, uint32_t r3) {
    asm volatile("stmatrix.sync.aligned.m8n8.x4.shared.b16 [%0], {%1,%2,%3,%4};" :: "r"(addr), "r"(r0), "r"(r1), "r"(r2), "r"(r3) : "memory");
}
template <int OFF> __device__ __forceinline__ uint32_t lds32_o(uint32_t addr) { uint32_t v; asm volatile("ld.shared.b32 %0, [%1+%2];" : "=r"(v) : "r"(addr), "n"(OFF) : "memory"); return v; }
__device__ __forceinline__ uint32_t lds32(uint32_t addr) { uint32_t v; asm volatile("ld.shared.b32 %0, [%1];" : "=r"(v) : "r"(addr) : "memory"); return v; }
__device__ __forceinline__ uint4 lds128(uint32_t addr) { uint4 v; asm volatile("ld.shared.v4.b32 {%0,%1,%2,%3}, [%4];" : "=r"(v.x), "=r"(v.y), "=r"(v.z), "=r"(v.w) : "r"(addr) : "memory"); return v; }
__device__ __forceinline__ void sts128(uint32_t addr, uint32_t a, uint32_t b, uint32_t c, uint32_t d) { asm volatile("st.shared.v4.b32 [%0], {%1,%2,%3,%4};" :: "r"(addr), "r"(a), "r"(b), "r"(c), "r"(d) : "memory"); }

__device__ __forceinline__ uint32_t bf2_mul(uint32_t a, uint32_t b) { uint32_t r; asm("mul.rn.bf16x2 %0, %1, %2;" : "=r"(r) : "r"(a), "r"(b)); return r; }
__device__ __forceinline__ uint32_t bf2_add(uint32_t a, uint32_t b) { uint32_t r; asm("add.rn.bf16x2 %0, %1, %2;" : "=r"(r) : "r"(a), "r"(b)); return r; }
__device__ __forceinline__ uint32_t bf2_sub(uint32_t a, uint32_t b) { uint32_t r; asm("sub.rn.bf16x2 %0, %1, %2;" : "=r"(r) : "r"(a), "r"(b)); return r; }
__device__ __forceinline__ uint32_t pack_bf2(float lo, float hi) { uint32_t r; asm("cvt.rn.bf16x2.f32 %0, %1, %2;" : "=r"(r) : "f"(hi), "f"(lo)); return r; }
__device__ __forceinline__ float bf_lo(uint32_t v) { return __uint_as_float(v << 16); }
__device__ __forceinline__ float bf_hi(uint32_t v) { return __uint_as_float(v & 0xFFFF0000u); }
__device__ __forceinline__ float silu_f(float x) {
    float e, r;
    asm("ex2.approx.ftz.f32 %0, %1;" : "=f"(e) : "f"(x * -1.4426950408889634f));
    asm("rcp.approx.ftz.f32 %0, %1;" : "=f"(r) : "f"(1.0f + e));
    return x * r;
}
__device__ __forceinline__ uint32_t silu_bf2(uint32_t v) { return pack_bf2(silu_f(bf_lo(v)), silu_f(bf_hi(v))); }


template <int I>
__device__ __forceinline__ void stage_piece(const uint32_t (&pg)[32], const uint32_t (&pu)[32], uint32_t stg_lane, uint32_t lrow7, uint32_t lgrp) {
    const uint32_t addr = stg_lane + (((2 * (I & 3) + lgrp) ^ lrow7) << 4);
    stsm_x4(addr, pg[4 * I], pg[4 * I + 1], pg[4 * I + 2], pg[4 * I + 3]);
    stsm_x4(addr + 8192, pu[4 * I], pu[4 * I + 1], pu[4 * I + 2], pu[4 * I + 3]);
}
__device__ __forceinline__ void stage_piece_dyn(int i, const uint32_t (&pg)[32], const uint32_t (&pu)[32], uint32_t stg_lane, uint32_t lrow7, uint32_t lgrp) {
    switch (i) {
        case 0: stage_piece<0>(pg, pu, stg_lane, lrow7, lgrp); break;
        case 1: stage_piece<1>(pg, pu, stg_lane, lrow7, lgrp); break;
        case 2: stage_piece<2>(pg, pu, stg_lane, lrow7, lgrp); break;
        case 3: stage_piece<3>(pg, pu, stg_lane, lrow7, lgrp); break;
        case 4: stage_piece<4>(pg, pu, stg_lane, lrow7, lgrp); break;
        case 5: stage_piece<5>(pg, pu, stg_lane, lrow7, lgrp); break;
        case 6: stage_piece<6>(pg, pu, stg_lane, lrow7, lgrp); break;
        default: stage_piece<7>(pg, pu, stg_lane, lrow7, lgrp); break;
    }
}
__device__ __forceinline__ void wgmma_128_lo(float (&d)[128], uint64_t a, uint64_t b, int scale_d) {
    asm volatile("{\n.reg .pred p;\nsetp.ne.b32 p, %66, 0;\n"
    "wgmma.mma_async.sync.aligned.m64n128k16.f32.bf16.bf16 "
    "{%0,%1,%2,%3,%4,%5,%6,%7,%8,%9,%10,%11,%12,%13,%14,%15,"
    "%16,%17,%18,%19,%20,%21,%22,%23,%24,%25,%26,%27,%28,%29,%30,%31,"
    "%32,%33,%34,%35,%36,%37,%38,%39,%40,%41,%42,%43,%44,%45,%46,%47,"
    "%48,%49,%50,%51,%52,%53,%54,%55,%56,%57,%58,%59,%60,%61,%62,%63},"
    "%64, %65, p, 1, 1, 0, 1;\n}\n"
    : H3_R64(0)
    : "l"(a), "l"(b), "r"(scale_d));
}

template <int N> __device__ __forceinline__ void wgmma_rs(float (&d)[128], const uint32_t (&a)[4], uint64_t b, int scale_d);
template <> __device__ __forceinline__ void wgmma_rs<64>(float (&d)[128], const uint32_t (&a)[4], uint64_t b, int scale_d) {
    asm volatile("{\n.reg .pred p;\nsetp.ne.b32 p, %37, 0;\nwgmma.mma_async.sync.aligned.m64n64k16.f32.bf16.bf16 {%0,%1,%2,%3,%4,%5,%6,%7,%8,%9,%10,%11,%12,%13,%14,%15,%16,%17,%18,%19,%20,%21,%22,%23,%24,%25,%26,%27,%28,%29,%30,%31}, {%32,%33,%34,%35}, %36, p, 1, 1, 0;\n}\n"
        : "+f"(d[0]), "+f"(d[1]), "+f"(d[2]), "+f"(d[3]), "+f"(d[4]), "+f"(d[5]), "+f"(d[6]), "+f"(d[7]), "+f"(d[8]), "+f"(d[9]), "+f"(d[10]), "+f"(d[11]), "+f"(d[12]), "+f"(d[13]), "+f"(d[14]), "+f"(d[15]), "+f"(d[16]), "+f"(d[17]), "+f"(d[18]), "+f"(d[19]), "+f"(d[20]), "+f"(d[21]), "+f"(d[22]), "+f"(d[23]), "+f"(d[24]), "+f"(d[25]), "+f"(d[26]), "+f"(d[27]), "+f"(d[28]), "+f"(d[29]), "+f"(d[30]), "+f"(d[31])
        : "r"(a[0]), "r"(a[1]), "r"(a[2]), "r"(a[3]), "l"(b), "r"(scale_d));
}
template <> __device__ __forceinline__ void wgmma_rs<128>(float (&d)[128], const uint32_t (&a)[4], uint64_t b, int scale_d) {
    asm volatile("{\n.reg .pred p;\nsetp.ne.b32 p, %69, 0;\nwgmma.mma_async.sync.aligned.m64n128k16.f32.bf16.bf16 {%0,%1,%2,%3,%4,%5,%6,%7,%8,%9,%10,%11,%12,%13,%14,%15,%16,%17,%18,%19,%20,%21,%22,%23,%24,%25,%26,%27,%28,%29,%30,%31,%32,%33,%34,%35,%36,%37,%38,%39,%40,%41,%42,%43,%44,%45,%46,%47,%48,%49,%50,%51,%52,%53,%54,%55,%56,%57,%58,%59,%60,%61,%62,%63}, {%64,%65,%66,%67}, %68, p, 1, 1, 0;\n}\n"
        : "+f"(d[0]), "+f"(d[1]), "+f"(d[2]), "+f"(d[3]), "+f"(d[4]), "+f"(d[5]), "+f"(d[6]), "+f"(d[7]), "+f"(d[8]), "+f"(d[9]), "+f"(d[10]), "+f"(d[11]), "+f"(d[12]), "+f"(d[13]), "+f"(d[14]), "+f"(d[15]), "+f"(d[16]), "+f"(d[17]), "+f"(d[18]), "+f"(d[19]), "+f"(d[20]), "+f"(d[21]), "+f"(d[22]), "+f"(d[23]), "+f"(d[24]), "+f"(d[25]), "+f"(d[26]), "+f"(d[27]), "+f"(d[28]), "+f"(d[29]), "+f"(d[30]), "+f"(d[31]), "+f"(d[32]), "+f"(d[33]), "+f"(d[34]), "+f"(d[35]), "+f"(d[36]), "+f"(d[37]), "+f"(d[38]), "+f"(d[39]), "+f"(d[40]), "+f"(d[41]), "+f"(d[42]), "+f"(d[43]), "+f"(d[44]), "+f"(d[45]), "+f"(d[46]), "+f"(d[47]), "+f"(d[48]), "+f"(d[49]), "+f"(d[50]), "+f"(d[51]), "+f"(d[52]), "+f"(d[53]), "+f"(d[54]), "+f"(d[55]), "+f"(d[56]), "+f"(d[57]), "+f"(d[58]), "+f"(d[59]), "+f"(d[60]), "+f"(d[61]), "+f"(d[62]), "+f"(d[63])
        : "r"(a[0]), "r"(a[1]), "r"(a[2]), "r"(a[3]), "l"(b), "r"(scale_d));
}
template <> __device__ __forceinline__ void wgmma_rs<192>(float (&d)[128], const uint32_t (&a)[4], uint64_t b, int scale_d) {
    asm volatile("{\n.reg .pred p;\nsetp.ne.b32 p, %101, 0;\nwgmma.mma_async.sync.aligned.m64n192k16.f32.bf16.bf16 {%0,%1,%2,%3,%4,%5,%6,%7,%8,%9,%10,%11,%12,%13,%14,%15,%16,%17,%18,%19,%20,%21,%22,%23,%24,%25,%26,%27,%28,%29,%30,%31,%32,%33,%34,%35,%36,%37,%38,%39,%40,%41,%42,%43,%44,%45,%46,%47,%48,%49,%50,%51,%52,%53,%54,%55,%56,%57,%58,%59,%60,%61,%62,%63,%64,%65,%66,%67,%68,%69,%70,%71,%72,%73,%74,%75,%76,%77,%78,%79,%80,%81,%82,%83,%84,%85,%86,%87,%88,%89,%90,%91,%92,%93,%94,%95}, {%96,%97,%98,%99}, %100, p, 1, 1, 0;\n}\n"
        : "+f"(d[0]), "+f"(d[1]), "+f"(d[2]), "+f"(d[3]), "+f"(d[4]), "+f"(d[5]), "+f"(d[6]), "+f"(d[7]), "+f"(d[8]), "+f"(d[9]), "+f"(d[10]), "+f"(d[11]), "+f"(d[12]), "+f"(d[13]), "+f"(d[14]), "+f"(d[15]), "+f"(d[16]), "+f"(d[17]), "+f"(d[18]), "+f"(d[19]), "+f"(d[20]), "+f"(d[21]), "+f"(d[22]), "+f"(d[23]), "+f"(d[24]), "+f"(d[25]), "+f"(d[26]), "+f"(d[27]), "+f"(d[28]), "+f"(d[29]), "+f"(d[30]), "+f"(d[31]), "+f"(d[32]), "+f"(d[33]), "+f"(d[34]), "+f"(d[35]), "+f"(d[36]), "+f"(d[37]), "+f"(d[38]), "+f"(d[39]), "+f"(d[40]), "+f"(d[41]), "+f"(d[42]), "+f"(d[43]), "+f"(d[44]), "+f"(d[45]), "+f"(d[46]), "+f"(d[47]), "+f"(d[48]), "+f"(d[49]), "+f"(d[50]), "+f"(d[51]), "+f"(d[52]), "+f"(d[53]), "+f"(d[54]), "+f"(d[55]), "+f"(d[56]), "+f"(d[57]), "+f"(d[58]), "+f"(d[59]), "+f"(d[60]), "+f"(d[61]), "+f"(d[62]), "+f"(d[63]), "+f"(d[64]), "+f"(d[65]), "+f"(d[66]), "+f"(d[67]), "+f"(d[68]), "+f"(d[69]), "+f"(d[70]), "+f"(d[71]), "+f"(d[72]), "+f"(d[73]), "+f"(d[74]), "+f"(d[75]), "+f"(d[76]), "+f"(d[77]), "+f"(d[78]), "+f"(d[79]), "+f"(d[80]), "+f"(d[81]), "+f"(d[82]), "+f"(d[83]), "+f"(d[84]), "+f"(d[85]), "+f"(d[86]), "+f"(d[87]), "+f"(d[88]), "+f"(d[89]), "+f"(d[90]), "+f"(d[91]), "+f"(d[92]), "+f"(d[93]), "+f"(d[94]), "+f"(d[95])
        : "r"(a[0]), "r"(a[1]), "r"(a[2]), "r"(a[3]), "l"(b), "r"(scale_d));
}
template <> __device__ __forceinline__ void wgmma_rs<256>(float (&d)[128], const uint32_t (&a)[4], uint64_t b, int scale_d) {
    asm volatile("{\n.reg .pred p;\nsetp.ne.b32 p, %133, 0;\nwgmma.mma_async.sync.aligned.m64n256k16.f32.bf16.bf16 {%0,%1,%2,%3,%4,%5,%6,%7,%8,%9,%10,%11,%12,%13,%14,%15,%16,%17,%18,%19,%20,%21,%22,%23,%24,%25,%26,%27,%28,%29,%30,%31,%32,%33,%34,%35,%36,%37,%38,%39,%40,%41,%42,%43,%44,%45,%46,%47,%48,%49,%50,%51,%52,%53,%54,%55,%56,%57,%58,%59,%60,%61,%62,%63,%64,%65,%66,%67,%68,%69,%70,%71,%72,%73,%74,%75,%76,%77,%78,%79,%80,%81,%82,%83,%84,%85,%86,%87,%88,%89,%90,%91,%92,%93,%94,%95,%96,%97,%98,%99,%100,%101,%102,%103,%104,%105,%106,%107,%108,%109,%110,%111,%112,%113,%114,%115,%116,%117,%118,%119,%120,%121,%122,%123,%124,%125,%126,%127}, {%128,%129,%130,%131}, %132, p, 1, 1, 0;\n}\n"
        : "+f"(d[0]), "+f"(d[1]), "+f"(d[2]), "+f"(d[3]), "+f"(d[4]), "+f"(d[5]), "+f"(d[6]), "+f"(d[7]), "+f"(d[8]), "+f"(d[9]), "+f"(d[10]), "+f"(d[11]), "+f"(d[12]), "+f"(d[13]), "+f"(d[14]), "+f"(d[15]), "+f"(d[16]), "+f"(d[17]), "+f"(d[18]), "+f"(d[19]), "+f"(d[20]), "+f"(d[21]), "+f"(d[22]), "+f"(d[23]), "+f"(d[24]), "+f"(d[25]), "+f"(d[26]), "+f"(d[27]), "+f"(d[28]), "+f"(d[29]), "+f"(d[30]), "+f"(d[31]), "+f"(d[32]), "+f"(d[33]), "+f"(d[34]), "+f"(d[35]), "+f"(d[36]), "+f"(d[37]), "+f"(d[38]), "+f"(d[39]), "+f"(d[40]), "+f"(d[41]), "+f"(d[42]), "+f"(d[43]), "+f"(d[44]), "+f"(d[45]), "+f"(d[46]), "+f"(d[47]), "+f"(d[48]), "+f"(d[49]), "+f"(d[50]), "+f"(d[51]), "+f"(d[52]), "+f"(d[53]), "+f"(d[54]), "+f"(d[55]), "+f"(d[56]), "+f"(d[57]), "+f"(d[58]), "+f"(d[59]), "+f"(d[60]), "+f"(d[61]), "+f"(d[62]), "+f"(d[63]), "+f"(d[64]), "+f"(d[65]), "+f"(d[66]), "+f"(d[67]), "+f"(d[68]), "+f"(d[69]), "+f"(d[70]), "+f"(d[71]), "+f"(d[72]), "+f"(d[73]), "+f"(d[74]), "+f"(d[75]), "+f"(d[76]), "+f"(d[77]), "+f"(d[78]), "+f"(d[79]), "+f"(d[80]), "+f"(d[81]), "+f"(d[82]), "+f"(d[83]), "+f"(d[84]), "+f"(d[85]), "+f"(d[86]), "+f"(d[87]), "+f"(d[88]), "+f"(d[89]), "+f"(d[90]), "+f"(d[91]), "+f"(d[92]), "+f"(d[93]), "+f"(d[94]), "+f"(d[95]), "+f"(d[96]), "+f"(d[97]), "+f"(d[98]), "+f"(d[99]), "+f"(d[100]), "+f"(d[101]), "+f"(d[102]), "+f"(d[103]), "+f"(d[104]), "+f"(d[105]), "+f"(d[106]), "+f"(d[107]), "+f"(d[108]), "+f"(d[109]), "+f"(d[110]), "+f"(d[111]), "+f"(d[112]), "+f"(d[113]), "+f"(d[114]), "+f"(d[115]), "+f"(d[116]), "+f"(d[117]), "+f"(d[118]), "+f"(d[119]), "+f"(d[120]), "+f"(d[121]), "+f"(d[122]), "+f"(d[123]), "+f"(d[124]), "+f"(d[125]), "+f"(d[126]), "+f"(d[127])
        : "r"(a[0]), "r"(a[1]), "r"(a[2]), "r"(a[3]), "l"(b), "r"(scale_d));
}

template <int I> __device__ __forceinline__ void conv_load_a(uint32_t (&a)[16][4], const uint32_t (&hx)[8]) {
    constexpr int IP = I >> 2, SG = I & 3;
    a[I][0] = lds32_o<-1024 * IP>(hx[2 * SG]); a[I][1] = lds32_o<-1024 * IP - 512>(hx[2 * SG]);
    a[I][2] = lds32_o<-1024 * IP>(hx[2 * SG + 1]); a[I][3] = lds32_o<-1024 * IP - 512>(hx[2 * SG + 1]);
    if constexpr (I < 15) conv_load_a<I + 1>(a, hx);
}
template <int I> __device__ __forceinline__ void conv_issue(float (&acc)[128], const uint32_t (&a)[16][4], uint64_t db) {
    wgmma_rs<256 - 64 * (I >> 2)>(acc, a[I], db + 64 * (I >> 2) + 2 * (I & 3), I != 0);
    if constexpr (I < 15) conv_issue<I + 1>(acc, a, db);
}
__device__ __forceinline__ void conv_frag_addr(uint32_t (&hx)[8], uint32_t copy_base, int w0, uint32_t xb) {
#pragma unroll
    for (int i = 0; i < 8; i++) { const uint32_t W = (uint32_t)(w0 - 4 * i); hx[i] = copy_base + ((W ^ (((W >> 5) & 3u) << 2) ^ xb) << 2); }
}

__device__ __forceinline__ void kv_cta(const Params& p, uint32_t sb, int j) {
    constexpr uint32_t IN_BYTES = 17408 + 16384, OFF_V = 17408;
    constexpr uint32_t OFF_OUT = 4 * IN_BYTES, OFF_TAPS = OFF_OUT + 4 * 16384;
    constexpr uint32_t B_INF = 0, B_INE = 32, B_OUTF = 64, B_OUTE = 96;
    const uint32_t bars = sb + OFF_BAR;
    const int tid = threadIdx.x, lane = tid & 31;
    if (tid == 0) {
        for (int s = 0; s < 4; s++) { mbar_init(bars + B_INF + 8 * s, 1); mbar_init(bars + B_INE + 8 * s, 8); mbar_init(bars + B_OUTF + 8 * s, 8); mbar_init(bars + B_OUTE + 8 * s, 1); }
        asm volatile("fence.mbarrier_init.release.cluster;" ::: "memory");
    }
    for (int i = tid; i < 512; i += 384) { const uint4 t = __ldg(reinterpret_cast<const uint4*>(p.shift_k) + i); sts128(sb + OFF_TAPS + i * 16, t.x, t.y, t.z, t.w); }
    __syncthreads();
    if (tid == 0) {
        const uint64_t pol = policy_evict_first();
#pragma unroll 1
        for (int i = 0; i < 64 + 3; i++) {
            if (i < 64) {
                const int bf = i & 3, t0 = j * 512 + (i >> 3) * 64, c0 = (i & 7) * 128;
                if (i >= 4) mbar_wait(bars + B_INE + 8 * bf, ((i >> 2) - 1) & 1);
                mbar_expect_tx(bars + B_INF + 8 * bf, 67 * 256 + 64 * 256);
                tma_2d_h(sb + bf * IN_BYTES, &p.tmK, c0, t0 - 3, bars + B_INF + 8 * bf, pol);
                tma_2d_h(sb + bf * IN_BYTES + OFF_V, &p.tmV, c0, t0, bars + B_INF + 8 * bf, pol);
            }
            if (i >= 3) {
                const int o = i - 3, bf = o & 3;
                mbar_wait(bars + B_OUTF + 8 * bf, (o >> 2) & 1);
                tma_store_2d(&p.tmKvT, sb + OFF_OUT + bf * 16384, 1984 - (j * 512 + (o >> 3) * 64), (o & 7) * 128);
                bulk_commit();
                asm volatile("cp.async.bulk.wait_group.read 1;" ::: "memory");
                if (o > 0) mbar_arrive(bars + B_OUTE + 8 * ((o - 1) & 3));
            }
        }
        bulk_wait_all();
        flag_add_after_bulk(p.flags + FL_KV * FLAG_STRIDE);
    } else if (tid >= 32) {
#pragma unroll 1
        for (int u = (tid >> 5) - 1; u < 512; u += 11) {
            const int i = u >> 3, bf = i & 3, o = u & 7;
            mbar_wait(bars + B_INF + 8 * bf, (i >> 2) & 1);
            if (i >= 4) mbar_wait(bars + B_OUTE + 8 * bf, ((i >> 2) - 1) & 1);
            const uint32_t out = sb + OFF_OUT + bf * 16384;
            const uint32_t odd = (lane >> 2) & 1, sel0 = odd ? 0x7632u : 0x5410u, sel1 = odd ? 0x5410u : 0x7632u;
            uint32_t kk[2][11], vv[2][8];
            uint4 sw[2];
#pragma unroll
            for (int it = 0; it < 2; it++) {
                const uint32_t rd = sb + bf * IN_BYTES + o * 8 * 256 + (it * 32 + lane) * 4;
#pragma unroll
                for (int r = 0; r < 11; r++) kk[it][r] = lds32(rd + r * 256);
#pragma unroll
                for (int r = 0; r < 8; r++) vv[it][r] = lds32(rd + OFF_V + r * 256);
                sw[it] = lds128(sb + OFF_TAPS + ((i & 7) * 64 + it * 32 + lane) * 16);
            }
#pragma unroll
            for (int it = 0; it < 2; it++) {
                const uint32_t w0 = __byte_perm(sw[it].x, sw[it].z, 0x5410), w1 = __byte_perm(sw[it].x, sw[it].z, 0x7632);
                const uint32_t w2 = __byte_perm(sw[it].y, sw[it].w, 0x5410), w3 = __byte_perm(sw[it].y, sw[it].w, 0x7632);
#pragma unroll
                for (int r = 0; r < 8; r++)
                    vv[it][r] = bf2_mul(bf2_add(bf2_add(bf2_add(bf2_mul(kk[it][r], w3), bf2_mul(kk[it][r + 1], w2)), bf2_mul(kk[it][r + 2], w1)), bf2_mul(kk[it][r + 3], w0)), vv[it][r]);
                const uint32_t r0 = 2 * (it * 32 + lane) + odd, r1 = r0 ^ 1;
                const uint32_t* v = vv[it];
                sts128(out + r0 * 128 + (((7 - o) ^ (r0 & 7)) << 4), __byte_perm(v[0], v[1], sel0), __byte_perm(v[2], v[3], sel0), __byte_perm(v[4], v[5], sel0), __byte_perm(v[6], v[7], sel0));
                sts128(out + r1 * 128 + (((7 - o) ^ (r1 & 7)) << 4), __byte_perm(v[0], v[1], sel1), __byte_perm(v[2], v[3], sel1), __byte_perm(v[4], v[5], sel1), __byte_perm(v[6], v[7], sel1));
            }
            fence_async_smem();
            __syncwarp();
            if (lane == 0) { mbar_arrive(bars + B_INE + 8 * bf); mbar_arrive(bars + B_OUTF + 8 * bf); }
        }
    }
}

__global__ void __launch_bounds__(384, 1) h3_kernel(const __grid_constant__ Params p) {
    extern __shared__ uint8_t smem_raw[];
    const uint32_t sb = (smem_u32(smem_raw) + 1023) & ~1023u;
    const uint32_t bars = sb + OFF_BAR;
    const int tid = threadIdx.x;
    const int wg = __shfl_sync(0xffffffffu, tid >> 7, 0);
    const int lane = tid & 31;
    const int cta = blockIdx.x;
    const int pair = cta >> 1;
    const uint32_t rank = cta & 1;

    if (cta >= NCTA) { kv_cta(p, sb, cta - NCTA); return; }

    uint32_t x[32];
    if (wg != 0) {
        const uint4* src = reinterpret_cast<const uint4*>(p.q + (size_t)(cta * 16 + ((tid >> 5) - 4) * 2 + (lane >> 4)) * D) + (lane & 15);
#pragma unroll
        for (int i = 0; i < 8; i++) { const uint4 t = __ldg(src + i * 16); x[4 * i] = t.x; x[4 * i + 1] = t.y; x[4 * i + 2] = t.z; x[4 * i + 3] = t.w; }
    }
    if (tid == 0) {
#pragma unroll 1
        for (int s = 0; s < 4; s++) { mbar_init(bars + BAR_FULLA + 8 * s, 1); mbar_init(bars + BAR_EMPTYA + 8 * s, 4); }
#pragma unroll 1
        for (int s = 0; s < 6; s++) { mbar_init(bars + BAR_FULLB + 8 * s, 1); mbar_init(bars + BAR_EMPTYB + 8 * s, 4); }
        mbar_init(bars + BAR_STGFULL, 8);
        mbar_init(bars + BAR_STGEMPTY, 1);
        mbar_init(bars + BAR_ALTFULL, 8);
        mbar_init(bars + BAR_ALT2FULL, 8);
        mbar_init(bars + BAR_OPFULL, 1);
        asm volatile("fence.mbarrier_init.release.cluster;" ::: "memory");
    }
    __syncthreads();
    cluster_arrive();

    const int grp = (pair < 4) ? 0 : (pair < 36) ? ((pair - 4) & 7) : 1 + (pair - 36) % 7;
    const int gj = (pair < 4) ? 4 + pair : (pair < 36) ? ((pair - 4) >> 3) : 4 + (pair - 36) / 7;
    const int m1 = 2 * grp + (int)rank, nb1 = gj;
    const int m2 = ((grp >> 2) << 3) | gj, pn = grp & 3;
    const int nh = 24 + pn;
    const int n2 = pn * 256 + (int)rank * 128;

    if (wg == 0) {
        asm volatile("setmaxnreg.dec.sync.aligned.u32 40;\n");
        const int warp = tid >> 5;
        if (warp == 0) {
            if (lane == 0) {
                const uint64_t pol = policy_evict_first();
                const int mrow1 = m1 * 128, mrow2 = m2 * 128 + (int)rank * 64, ngh = nh * 2 + (int)rank;
                const CUtensorMap* tmW = rank ? &p.tmWu2 : &p.tmWg2;
                const uint32_t woff = 16384 + rank * 16384;
                cluster_wait();
#pragma unroll 1
                for (int j = 0; j < 4; j++) {
                    const uint32_t full = bars + BAR_FULLA + 8 * j;
                    mbar_expect_tx(full, A_STAGE);
                    tma_3d_mc_h(sb + j * A_STAGE + woff, tmW, 0, j * 64, nb1 * 2, full, pol);
                }
                flag_wait(p.flags + (FL_XN + m1) * FLAG_STRIDE, 64);
#pragma unroll 1
                for (int j = 0; j < 4; j++) tma_2d(sb + j * A_STAGE, &p.tmXn128, j * 64, mrow1, bars + BAR_FULLA + 8 * j);
#pragma unroll 1
                for (int g = 4; g < 48; g++) {
                    const int st = g & 3, k0 = (g & 15) * 64, ng = ((g >> 4) * 8 + nb1) * 2;
                    const uint32_t full = bars + BAR_FULLA + 8 * st, a = sb + st * A_STAGE;
                    mbar_wait(bars + BAR_EMPTYA + 8 * st, ((g >> 2) - 1) & 1);
                    mbar_expect_tx(full, A_STAGE);
                    tma_2d(a, &p.tmXn128, k0, mrow1, full);
                    tma_3d_mc_h(a + woff, tmW, 0, k0, ng, full, pol);
                    if (g == 3 * ((cta & 31) >> 2) - 2) { pf_bulk_h(p.k + (size_t)cta * 16 * D, 32768, pol); pf_bulk_h(p.v + (size_t)cta * 16 * D, 32768, pol); }
                }
                flag_wait(p.flags + (FL_XN + m2) * FLAG_STRIDE, 64);
                pf_bulk_h(p.ssm_k + (size_t)cta * 8 * S, 32768, pol);
                int st = 0; uint32_t ph = 1;
#pragma unroll 1
                for (int e = 0; e < 16; e++) {
                    const uint32_t full = bars + BAR_FULLB + 8 * st, a = sb + st * B_STAGE;
                    if (e < 6) {
                        if (e != 2 && e != 5) mbar_wait(bars + BAR_EMPTYA + 8 * (e - (e >= 3)), 1);
                    } else {
                        mbar_wait(bars + BAR_EMPTYB + 8 * st, ph);
                    }
                    mbar_expect_tx(full, B_STAGE);
                    tma_2d_mc(a + rank * 8192, &p.tmXn64, e * 64, mrow2, full);
                    tma_3d_h(a + 16384, &p.tmWg1, 0, e * 64, ngh, full, pol);
                    tma_3d_h(a + 24576, &p.tmWu1, 0, e * 64, ngh, full, pol);
                    if (++st == 6) { st = 0; ph ^= 1; }
                }
                mbar_wait(bars + BAR_EMPTYB + 8 * ST_H, 1);
                mbar_expect_tx(bars + BAR_FULLB + 8 * ST_H, 32768);
                bulk_g2s_h(sb + ST_H * B_STAGE, p.ssm_k + (size_t)cta * 8 * S, 32768, bars + BAR_FULLB + 8 * ST_H, pol);
                unsigned kv_ready;
                asm volatile("ld.acquire.gpu.global.u32 %0, [%1];" : "=r"(kv_ready) : "l"(p.flags + FL_KV * FLAG_STRIDE) : "memory");
#pragma unroll 1
                for (int pass = 0; pass < 2; pass++) {
                    if ((pass == 0) == (kv_ready >= 4)) {
                        mbar_wait(bars + BAR_EMPTYB + 8 * ST_U, 1);
                        flag_wait(p.flags + FL_KV * FLAG_STRIDE, 4);
                        mbar_expect_tx(bars + BAR_FULLB + 8 * ST_U, 32768);
#pragma unroll 1
                        for (int ch = 0; ch < 8; ch++) bulk_g2s_h(sb + ST_U * B_STAGE + ch * U_PITCH, p.kvT + (size_t)(cta * 8 + ch) * S, 4096, bars + BAR_FULLB + 8 * ST_U, pol);
                    }
                    if (pass == 0) {
#pragma unroll 1
                        for (int c = 0; c < 4; c++) { mbar_wait(bars + BAR_EMPTYB + 8 * c, 0); mbar_arrive(bars + BAR_FULLB + 8 * c); }
                    }
                }
                flag_wait(p.flags + (FL_H + m2) * FLAG_STRIDE, 16);
                int i6 = 0; uint32_t rho = 0;
#pragma unroll 1
                for (int kb = 0; kb < 56; kb++) {
                    const int sg = (0x512034 >> (4 * i6)) & 15;
                    const uint32_t par = ((0x21u >> i6) & 1u) ^ rho;
                    const uint32_t full = bars + BAR_FULLB + 8 * sg, a = sb + sg * B_STAGE;
                    mbar_wait(bars + BAR_EMPTYB + 8 * sg, par ^ 1);
                    if (kb == 32) flag_wait(p.flags + (FL_H2 + m2) * FLAG_STRIDE, 16);
                    mbar_expect_tx(full, B_STAGE);
                    tma_2d_mc(a + rank * 8192, &p.tmH64, kb * 64, mrow2, full);
                    tma_3d(a + 16384, &p.tmWd, 0, kb * 64, n2 >> 6, full);
                    if (++i6 == 6) { i6 = 0; rho ^= 1; }
                }
                mbar_wait(bars + BAR_EMPTYB + 0, 0);
                mbar_expect_tx(bars + BAR_FULLB + 0, 32768);
                tma_2d(sb, &p.tmX128, n2, m2 * 128, bars + BAR_FULLB + 0);
                tma_2d(sb + 16384, &p.tmX128, n2 + 64, m2 * 128, bars + BAR_FULLB + 0);
                mbar_wait(bars + BAR_OPFULL, 0);
                unsigned old;
                asm volatile("atom.acq_rel.gpu.global.add.u32 %0, [%1], 1;" : "=r"(old) : "l"(p.flags + FL_DONE * FLAG_STRIDE) : "memory");
                if (old == NCTA - 1) {
#pragma unroll 1
                    for (int i = 0; i < FL_COUNT; i++) p.flags[i * FLAG_STRIDE] = 0;
                }
            } else {
                cluster_wait();
            }
        } else {
            cluster_wait();
            const int wt = tid - 32;
#pragma unroll 1
            for (int Ri = 0; Ri < 7; Ri++) {
                const int R = (Ri == 5) ? 6 : (Ri == 6) ? 5 : Ri;
                const uint32_t buf = (R == 4) ? sb + ST_ALT2 * B_STAGE : (R == 6) ? sb + ST_ALT * B_STAGE : sb + OFF_STG;
                mbar_wait_idle(bars + ((R == 4) ? BAR_ALT2FULL : (R == 6) ? BAR_ALTFULL : BAR_STGFULL), (R < 4) ? (R & 1) : 0);
#pragma unroll 1
                for (int i0 = wt; i0 < 1024; i0 += 2 * 96) {
                    const int i1 = i0 + 96;
                    const uint32_t a0 = buf + (i0 >> 9) * 16384 + (i0 & 511) * 16;
                    const uint32_t a1 = (i1 < 1024) ? buf + (i1 >> 9) * 16384 + (i1 & 511) * 16 : a0;
                    uint4 g0 = lds128(a0), u0 = lds128(a0 + 8192), g1 = lds128(a1), u1 = lds128(a1 + 8192);
                    g0.x = bf2_mul(silu_bf2(g0.x), u0.x); g0.y = bf2_mul(silu_bf2(g0.y), u0.y); g0.z = bf2_mul(silu_bf2(g0.z), u0.z); g0.w = bf2_mul(silu_bf2(g0.w), u0.w);
                    g1.x = bf2_mul(silu_bf2(g1.x), u1.x); g1.y = bf2_mul(silu_bf2(g1.y), u1.y); g1.z = bf2_mul(silu_bf2(g1.z), u1.z); g1.w = bf2_mul(silu_bf2(g1.w), u1.w);
                    sts128(a0, g0.x, g0.y, g0.z, g0.w);
                    if (i1 < 1024) sts128(a1, g1.x, g1.y, g1.z, g1.w);
                }
                fence_async_smem();
                bar_sync(4, 96);
                if (wt == 0) {
                    const int mm = (R < 6) ? m1 : m2;
                    const int col = (R < 6) ? (8 * (R >> 1) + nb1) * 128 + (R & 1) * 64 : nh * 128 + (int)rank * 64;
                    tma_store_2d(&p.tmH64, buf, col, mm * 128);
                    tma_store_2d(&p.tmH64, buf + 16384, col, mm * 128 + 64);
                    bulk_commit();
                    bulk_wait_read();
                    if (R != 4 && R != 6) mbar_arrive(bars + BAR_STGEMPTY);
                    else {
                        const uint32_t eb = bars + BAR_EMPTYB + 8 * ((R == 4) ? ST_ALT2 : ST_ALT);
                        mbar_arrive_cta(eb, 0); mbar_arrive_cta(eb, 0); mbar_arrive_cta(eb, 1); mbar_arrive_cta(eb, 1);
                    }
                    if (R == 1 || R == 3 || R >= 5) {
                        bulk_wait_all();
                        flag_add_after_bulk(p.flags + ((R < 4 ? FL_H : FL_H2) + mm) * FLAG_STRIDE);
                    }
                }
            }
            if (wt == 0) {
                mbar_wait(bars + BAR_FULLB + 8 * 3, 0); mbar_wait(bars + BAR_FULLB + 8 * 3, 1); mbar_wait(bars + BAR_FULLB + 8 * 3, 0);
                pf_2d(&p.tmX128, n2, m2 * 128); pf_2d(&p.tmX128, n2 + 64, m2 * 128);
                flag_wait(p.flags + (FL_Y + (n2 >> 7)) * FLAG_STRIDE, 128);
                mbar_expect_tx(bars + BAR_OPFULL, 32768);
                tma_2d(sb + OFF_STG, &p.tmY2T, 1984 - m2 * 128, n2, bars + BAR_OPFULL);
                tma_2d(sb + OFF_STG + 16384, &p.tmY2T, 1920 - m2 * 128, n2, bars + BAR_OPFULL);
            }
        }
        __syncwarp();
        cluster_sync();
    } else {
        asm volatile("setmaxnreg.inc.sync.aligned.u32 232;\n");
        const int cw = wg - 1;
        const int w = (tid >> 5) & 3;
        const int wtid = tid & 127;

        {
            const int rl = (cw * 4 + w) * 2 + (lane >> 4);
            const uint32_t src = sb + OFF_STG + rl * 2048 + (lane & 15) * 16;
            float s0 = 0.f, s1 = 0.f, s2 = 0.f, s3 = 0.f;
#pragma unroll
            for (int i = 0; i < 32; i += 2) { s0 += bf_lo(x[i]); s1 += bf_hi(x[i]); s2 += bf_lo(x[i + 1]); s3 += bf_hi(x[i + 1]); }
            float s = (s0 + s1) + (s2 + s3);
#pragma unroll
            for (int o = 8; o > 0; o >>= 1) s += __shfl_xor_sync(0xffffffffu, s, o);
            const float mu = s * (1.0f / D);
            s0 = s1 = s2 = s3 = 0.f;
#pragma unroll
            for (int i = 0; i < 32; i += 2) {
                const float a = bf_lo(x[i]) - mu, b = bf_hi(x[i]) - mu, c = bf_lo(x[i + 1]) - mu, d = bf_hi(x[i + 1]) - mu;
                s0 = fmaf(a, a, s0); s1 = fmaf(b, b, s1); s2 = fmaf(c, c, s2); s3 = fmaf(d, d, s3);
            }
            float v = (s0 + s1) + (s2 + s3);
#pragma unroll
            for (int o = 8; o > 0; o >>= 1) v += __shfl_xor_sync(0xffffffffu, v, o);
            const uint32_t mu2 = pack_bf2(mu, mu);
            const float vb = bf_lo(pack_bf2(v * (1.0f / D), 0.f));
            const float ve = bf_lo(pack_bf2(vb + 1e-5f, 0.f));
            const float sd = bf_lo(pack_bf2(sqrtf(ve), 0.f));
            const float inv = __frcp_rn(sd);
#pragma unroll
            for (int i = 0; i < 8; i++) {
                uint32_t oo[4];
#pragma unroll
                for (int e = 0; e < 4; e++) { const uint32_t dd = bf2_sub(x[4 * i + e], mu2); oo[e] = pack_bf2(bf_lo(dd) * inv, bf_hi(dd) * inv); }
                sts128(src + i * 256, oo[0], oo[1], oo[2], oo[3]);
            }
            if ((lane & 15) == 0) asm volatile("st.shared.v2.b32 [%0], {%1, %2};" :: "r"(bars + OFF_STAT + rl * 8), "r"(mu2), "r"(__float_as_uint(inv)) : "memory");
            fence_async_smem();
            __syncwarp();
            if (lane == 0) {
                bulk_s2g(p.xn + (size_t)(cta * 16 + (cw * 4 + w) * 2) * D, sb + OFF_STG + (cw * 4 + w) * 4096, 4096);
                bulk_s2g(p.stats + cta * 16 + (cw * 4 + w) * 2, bars + OFF_STAT + (cw * 4 + w) * 16, 16);
                bulk_commit();
                bulk_wait_all();
                flag_add_after_bulk(p.flags + (FL_XN + (cta >> 3)) * FLAG_STRIDE);
            }
            bar_sync(3, 256);
        }
        cluster_wait();

        const uint32_t lrow = w * 16 + (lane & 7) + ((lane >> 3) & 1) * 8;
        const uint32_t lrow7 = lane & 7;
        const uint32_t lgrp = lane >> 4;
        const uint32_t stg_lane = sb + OFF_STG + cw * 16384 + lrow * 128;
        const uint64_t descA = make_desc(sb + cw * 8192, 16, 1024);
        const uint64_t descB = make_desc(sb + 16384, 8192, 1024);

        int st = 0; uint32_t ph = 0;
        uint32_t pg[32], pu[32], qg[16], qu[16];
        {
            float acc[128];
            int prev = 0;
#pragma unroll 1
            for (int g = 0; g < 64; g++) {
                const int kb = g & 15;
                if (g < 48) {
                    const int sa = g & 3;
                    mbar_wait(bars + BAR_FULLA + 8 * sa, (g >> 2) & 1);
                    const uint64_t da = descA + sa * (A_STAGE >> 4), db = descB + sa * (A_STAGE >> 4);
                    wg_fence();
                    wgmma_256(acc, da, db, kb != 0);
#pragma unroll
                    for (int k = 1; k < 4; k++) wgmma_256(acc, da + k * 2, db + k * 128, 1);
                    wg_commit();
                } else {
                    mbar_wait(bars + BAR_FULLB + 8 * st, ph);
                    const uint64_t da = descA + st * (B_STAGE >> 4), db = descB + st * (B_STAGE >> 4);
                    wg_fence();
                    wgmma_128_lo(acc, da, db, kb != 0);
#pragma unroll
                    for (int k = 1; k < 4; k++) wgmma_128_lo(acc, da + k * 2, db + k * 128, 1);
                    wg_commit();
                }
                wg_wait<1>();
                if (kb > 0) {
                    if (wtid < 2) mbar_arrive_cta(bars + ((g > 48) ? BAR_EMPTYB + 8 * prev : BAR_EMPTYA + 8 * ((g - 1) & 3)), wtid);
                }
                if (g >= 48) { prev = st; if (++st == 6) { st = 0; ph ^= 1; } }
                if (g >= 16 && g < 48) {
                    const int pc = (kb < 4) ? kb : ((kb >= 9 && kb < 13) ? kb - 5 : -1);
                    if (pc >= 0) {
                        if (pc == 0 && g >= 32) mbar_wait(bars + BAR_STGEMPTY, 1);
                        if (pc == 4) mbar_wait(bars + BAR_STGEMPTY, 0);
                        stage_piece_dyn(pc, pg, pu, stg_lane, lrow7, lgrp);
                        if ((pc & 3) == 3) { __syncwarp(); if (lane == 0) mbar_arrive(bars + BAR_STGFULL); }
                    }
                }
                if (kb == 15 && g < 48) {
                    wg_wait<0>();
                    if (wtid < 2) mbar_arrive_cta(bars + BAR_EMPTYA + 24, wtid);
#pragma unroll
                    for (int i = 0; i < 32; i++) { pg[i] = pack_bf2(acc[2 * i], acc[2 * i + 1]); pu[i] = pack_bf2(acc[64 + 2 * i], acc[64 + 2 * i + 1]); }
                }
            }
            wg_wait<0>();
            if (wtid < 2) mbar_arrive_cta(bars + BAR_EMPTYB + 8 * prev, wtid);
#pragma unroll
            for (int i = 0; i < 16; i++) { qg[i] = pack_bf2(acc[2 * i], acc[2 * i + 1]); qu[i] = pack_bf2(acc[32 + 2 * i], acc[32 + 2 * i + 1]); }
        }
        mbar_wait(bars + BAR_FULLB + 8 * ST_ALT2, 1);
        {
            const uint32_t alt_lane = sb + ST_ALT2 * B_STAGE + cw * 16384 + lrow * 128;
            stage_piece<0>(pg, pu, alt_lane, lrow7, lgrp); stage_piece<1>(pg, pu, alt_lane, lrow7, lgrp);
            stage_piece<2>(pg, pu, alt_lane, lrow7, lgrp); stage_piece<3>(pg, pu, alt_lane, lrow7, lgrp);
            __syncwarp(); if (lane == 0) mbar_arrive(bars + BAR_ALT2FULL);
        }
        mbar_wait(bars + BAR_STGEMPTY, 1);
        stage_piece<4>(pg, pu, stg_lane, lrow7, lgrp); stage_piece<5>(pg, pu, stg_lane, lrow7, lgrp);
        stage_piece<6>(pg, pu, stg_lane, lrow7, lgrp); stage_piece<7>(pg, pu, stg_lane, lrow7, lgrp);
        __syncwarp(); if (lane == 0) mbar_arrive(bars + BAR_STGFULL);
        mbar_wait(bars + BAR_FULLB + 8 * ST_ALT, 1);
        {
            const uint32_t alt_lane = sb + ST_ALT * B_STAGE + cw * 16384 + lrow * 128;
#pragma unroll
            for (int i = 0; i < 4; i++) {
                const uint32_t addr = alt_lane + (((2 * i + lgrp) ^ lrow7) << 4);
                stsm_x4(addr, qg[4 * i], qg[4 * i + 1], qg[4 * i + 2], qg[4 * i + 3]);
                stsm_x4(addr + 8192, qu[4 * i], qu[4 * i + 1], qu[4 * i + 2], qu[4 * i + 3]);
            }
            __syncwarp(); if (lane == 0) mbar_arrive(bars + BAR_ALTFULL);
        }
        {
            const int r = lane >> 2, c4 = lane & 3;
            mbar_wait(bars + BAR_FULLB + 8 * ST_H, 0);
            mbar_wait(bars + BAR_FULLB + 8 * ST_C0, 1);
            mbar_wait(bars + BAR_FULLB + 8 * ST_C1, 1);
            {
                const uint32_t sH = sb + ST_H * B_STAGE + (cw * 4 + w) * 4096;
                const uint32_t sA = sb + (w >> 1) * B_STAGE + ((w & 1) * 2 + cw) * 8192, sB = sA + 4096;
                uint4 hv[8]; uint32_t hp[8];
#pragma unroll
                for (int i = 0; i < 8; i++) {
                    const int Q = i * 32 + lane;
                    hv[i] = lds128(sH + (255 - Q) * 16);
                    hp[i] = lds32(sH + (254 - Q) * 16 + 12);
                }
                if (lane == 31) hp[7] = 0;
                const uint32_t qs = (uint32_t)(lane ^ ((lane >> 3) & 3)) * 16;
#pragma unroll
                for (int i = 0; i < 8; i++) {
                    const uint4 a = hv[i];
                    const uint32_t prev = hp[i];
                    sts128(sA + i * 512 + qs, __byte_perm(a.w, 0, 0x1032), __byte_perm(a.z, 0, 0x1032), __byte_perm(a.y, 0, 0x1032), __byte_perm(a.x, 0, 0x1032));
                    sts128(sB + i * 512 + (qs ^ 64), __byte_perm(a.w, a.z, 0x7610), __byte_perm(a.z, a.y, 0x7610), __byte_perm(a.y, a.x, 0x7610), __byte_perm(a.x, prev, 0x7610));
                }
            }
            mbar_wait(bars + BAR_FULLB + 8 * ST_U, 0);
            if (lane < 8) sts128(sb + ST_U * B_STAGE + (cw * 4 + w) * U_PITCH + 4096 + lane * 16, 0, 0, 0, 0);
            fence_async_smem();
            bar_sync(1 + cw, 128);
            if (wtid < 2) mbar_arrive_cta(bars + BAR_EMPTYB + 8 * ST_H, wtid);
            if (cw == 1) bar_arrive(5, 256);
            const uint32_t podd = r & 1, b0 = (r >> 1) & 1, b1 = r >> 2;
            const int w0 = 1023 - w + c4 - 32 * (r >> 1);
            const uint32_t cpy = podd ? 0u : 4096u, xb = podd ? 0u : 16u;
            const int y0 = 2 * w + (int)podd - 2 * c4;
            const uint32_t mask0 = (r >> 1) ? 0xFFFFFFFFu : ((y0 >= 0 ? 0x0000FFFFu : 0u) | (y0 >= 1 ? 0xFFFF0000u : 0u));
            uint32_t a[16][4];
            {
                uint32_t hx[8];
                conv_frag_addr(hx, sb + cw * 8192 + cpy, w0, xb);
                conv_load_a<0>(a, hx);
                a[0][0] &= mask0;
            }
            const uint2 dq = __ldg(reinterpret_cast<const uint2*>(p.ssm_D + cta * 8 + cw * 4));
            auto conv_finish = [&](int cp) {
                const uint32_t sA = sb + (cp >> 1) * B_STAGE + ((cp & 1) * 2 + cw) * 8192;
                const uint32_t sU = sb + ST_U * B_STAGE + (cw * 4 + cp) * U_PITCH;
                const uint32_t dw = (cp & 2) ? dq.y : dq.x;
                const uint32_t d2 = __byte_perm(dw, 0, (cp & 1) ? 0x3232 : 0x1010);
#pragma unroll
                for (int i = 0; i < 2; i++) {
                    const uint32_t beta = 64 * w + 32 * i + lane;
                    const uint4 kv = lds128(sU + beta * 16);
                    const uint32_t y0w = lds32_o<0>(sA + beta * 4), y1w = lds32_o<1024>(sA + beta * 4), y2w = lds32_o<2048>(sA + beta * 4), y3w = lds32_o<3072>(sA + beta * 4);
                    sts128(sU + beta * 16, bf2_add(y0w, bf2_mul(kv.x, d2)), bf2_add(y1w, bf2_mul(kv.y, d2)), bf2_add(y2w, bf2_mul(kv.z, d2)), bf2_add(y3w, bf2_mul(kv.w, d2)));
                }
            };
            auto conv_store = [&](int cp) {
                const int ch = cw * 4 + cp;
                fence_async_smem();
                __syncwarp();
                if (lane == 0) { bulk_s2g(p.y2T + (size_t)(cta * 8 + ch) * S + w * 512, sb + ST_U * B_STAGE + ch * U_PITCH + w * 1024, 1024); bulk_commit(); }
                if (cp & 1) { bar_sync(1 + cw, 128); if (wtid < 2) mbar_arrive_cta(bars + BAR_EMPTYB + 8 * (cp >> 1), wtid); }
            };
#pragma unroll 1
            for (int ci = 0; ci < 4; ci++) {
                const int k = 2 * ci + cw;
                float acc[128];
                bar_sync(5 + cw, 256);
                wg_fence();
                conv_issue<0>(acc, a, make_desc_noswz(sb + ST_U * B_STAGE + (cw * 4 + ci) * U_PITCH, 16, 128));
                wg_commit();
                if (k < 7) bar_arrive(5 + (cw ^ 1), 256);
                if (ci > 0) conv_finish(ci - 1);
                wg_wait<0>();
                if (ci > 0) conv_store(ci - 1);
                float f[16];
                {
                    float wv[34];
#pragma unroll
                    for (int i = 0; i < 16; i++) {
#pragma unroll
                        for (int jj = 0; jj < 2; jj++) {
                            const float ve = acc[8 * i + jj] + ((2 * i + 4 < 32) ? acc[4 * (2 * i + 4) + 2 + jj] : 0.f);
                            const float vo = acc[8 * i + 4 + jj] + ((2 * i + 5 < 32) ? acc[4 * (2 * i + 5) + 2 + jj] : 0.f);
                            const float vn = (i < 15) ? acc[8 * i + 8 + jj] + ((2 * i + 6 < 32) ? acc[4 * (2 * i + 6) + 2 + jj] : 0.f) : 0.f;
                            wv[2 * i + jj] = (b0 ? vn : ve) + __shfl_xor_sync(0xffffffffu, vo, 8);
                        }
                    }
                    wv[32] = wv[33] = 0.f;
#pragma unroll
                    for (int kk = 0; kk < 8; kk++)
#pragma unroll
                        for (int jj = 0; jj < 2; jj++)
                            f[2 * kk + jj] = (b1 ? wv[4 * kk + 4 + jj] : wv[4 * kk + jj]) + __shfl_xor_sync(0xffffffffu, wv[4 * kk + 2 + jj], 16);
                }
                {
                    const uint32_t sA = sb + (ci >> 1) * B_STAGE + ((ci & 1) * 2 + cw) * 8192;
#pragma unroll
                    for (int kk = 0; kk < 8; kk++) {
                        const float keep = podd ? f[2 * kk + 1] : f[2 * kk];
                        const float recv = __shfl_xor_sync(0xffffffffu, podd ? f[2 * kk] : f[2 * kk + 1], 4);
                        const uint32_t yw = pack_bf2(podd ? recv : keep, podd ? keep : recv);
                        asm volatile("st.shared.b32 [%0], %1;" :: "r"(sA + w * 1024 + (32 * kk + 8 * (r >> 1) + 2 * c4 + podd) * 4), "r"(yw) : "memory");
                    }
                }
                if (ci < 3) {
                    uint32_t hx[8];
                    conv_frag_addr(hx, sb + ((ci + 1) >> 1) * B_STAGE + (((ci + 1) & 1) * 2 + cw) * 8192 + cpy, w0, xb);
                    conv_load_a<0>(a, hx);
                    a[0][0] &= mask0;
                }
            }
            bar_sync(1 + cw, 128);
            conv_finish(3);
            conv_store(3);
            if (lane == 0) bulk_wait_read();
            bar_sync(1 + cw, 128);
            if (wtid < 2) mbar_arrive_cta(bars + BAR_EMPTYB + 8 * ST_U, wtid);
        }
        {
            float acc[64];
            const int srow = m2 * 128 + cw * 64 + w * 16 + (lane >> 2);
            const uint2 st0 = __ldcg(p.stats + srow), st1 = __ldcg(p.stats + srow + 8);
            int i6 = 0, prev = 0; uint32_t rho = 0;
#pragma unroll 1
            for (int kb = 0; kb < 56; kb++) {
                const int sg = (0x512034 >> (4 * i6)) & 15;
                mbar_wait(bars + BAR_FULLB + 8 * sg, ((0x21u >> i6) & 1u) ^ rho);
                const uint64_t da = descA + sg * (B_STAGE >> 4), db = descB + sg * (B_STAGE >> 4);
                wg_fence();
                wgmma_128(acc, da, db, kb != 0);
#pragma unroll
                for (int k = 1; k < 4; k++) wgmma_128(acc, da + k * 2, db + k * 128, 1);
                wg_commit();
                                if (kb == 8 && lane == 0) { bulk_wait_all(); flag_add_after_bulk(p.flags + (FL_Y + (cta >> 4)) * FLAG_STRIDE); }
                wg_wait<1>();
                if (kb > 0 && wtid < 2) mbar_arrive_cta(bars + BAR_EMPTYB + 8 * prev, wtid);
                prev = sg;
                if (++i6 == 6) { i6 = 0; rho ^= 1; }
            }
            cluster_arrive();
            mbar_wait(bars + BAR_OPFULL, 0);
            wg_wait<0>();
            mbar_wait(bars + BAR_FULLB + 0, 1);
            const float inv0 = __uint_as_float(st0.y), inv1 = __uint_as_float(st1.y);
            const uint32_t ycol = sb + OFF_STG + cw * 16384 + (((7 - 2 * w - ((lane >> 3) & 1)) ^ lrow7) << 4) + lrow7 * 128;
            const uint32_t xrow = sb + (cw * 64 + lrow) * 128;
#pragma unroll 1
            for (int g2 = 0; g2 < 2; g2++) {
#pragma unroll
                for (int hh = 0; hh < 4; hh++) {
                    const uint32_t grp = hh * 2 + lgrp;
                    const uint32_t xa = xrow + g2 * 16384 + ((grp ^ lrow7) << 4);
                    uint32_t x[4], y[4], o[4];
                    ldsm_x4(xa, x[0], x[1], x[2], x[3]);
                    ldsm_x4_t(ycol + (g2 * 8 + grp) * 1024, y[0], y[1], y[2], y[3]);
#pragma unroll
                    for (int i = 0; i < 4; i++) {
                        const uint32_t dd = bf2_sub(x[i], (i & 1) ? st1.x : st0.x);
                        const float iv = (i & 1) ? inv1 : inv0;
                        const uint32_t xn = pack_bf2(bf_lo(dd) * iv, bf_hi(dd) * iv);
                        o[i] = bf2_add(x[i], bf2_mul(bf2_mul(xn, y[i]), silu_bf2(pack_bf2(acc[8 * hh + 2 * i], acc[8 * hh + 2 * i + 1]))));
                    }
                    stsm_x4(xa, o[0], o[1], o[2], o[3]);
                }
#pragma unroll
                for (int i = 0; i < 32; i++) acc[i] = acc[i + 32];
                fence_async_smem();
                bar_sync(1 + cw, 128);
                if (wtid == 0) { tma_store_2d(&p.tmOut64, sb + g2 * 16384 + cw * 8192, n2 + g2 * 64, m2 * 128 + cw * 64); bulk_commit(); }
            }
            if (wtid == 0) bulk_wait_read();
        }
        cluster_wait_end();
    }
}

typedef CUresult (*EncodeTiledFn)(CUtensorMap*, CUtensorMapDataType, cuuint32_t, void*, const cuuint64_t*, const cuuint64_t*,
                                  const cuuint32_t*, const cuuint32_t*, CUtensorMapInterleave, CUtensorMapSwizzle,
                                  CUtensorMapL2promotion, CUtensorMapFloatOOBfill);

static void make_map(EncodeTiledFn enc, CUtensorMap* m, const void* ptr, int rank, const uint64_t* dims, const uint64_t* strides, const uint32_t* box,
                     CUtensorMapSwizzle swz = CU_TENSOR_MAP_SWIZZLE_128B) {
    cuuint64_t d[3], s[2];
    cuuint32_t b[3], es[3] = {1, 1, 1};
    for (int i = 0; i < rank; i++) { d[i] = dims[i]; b[i] = box[i]; }
    for (int i = 0; i + 1 < rank; i++) s[i] = strides[i];
    CUresult r = enc(m, CU_TENSOR_MAP_DATA_TYPE_BFLOAT16, rank, const_cast<void*>(ptr), d, s, b, es, CU_TENSOR_MAP_INTERLEAVE_NONE,
                     swz, CU_TENSOR_MAP_L2_PROMOTION_L2_128B, CU_TENSOR_MAP_FLOAT_OOB_FILL_NONE);
    if (r != CUDA_SUCCESS) fprintf(stderr, "cuTensorMapEncodeTiled failed: %d\n", (int)r);
}
static void map2d(EncodeTiledFn enc, CUtensorMap* m, const void* ptr, uint64_t cols, uint64_t rows, uint32_t box_rows) {
    const uint64_t d[2] = {cols, rows}, s[1] = {cols * 2};
    const uint32_t b[2] = {64, box_rows};
    make_map(enc, m, ptr, 2, d, s, b);
}
static void map3d(EncodeTiledFn enc, CUtensorMap* m, const void* ptr, uint64_t cols, uint64_t rows, uint32_t groups) {
    const uint64_t d[3] = {64, rows, cols / 64}, s[2] = {cols * 2, 128};
    const uint32_t b[3] = {64, 64, groups};
    make_map(enc, m, ptr, 3, d, s, b);
}

}

extern "C" void kernel_launch(void* const* d_in, const int* in_sizes, int n_in, void* d_out, int out_size) {
    using namespace h3;
    (void)in_sizes; (void)n_in; (void)out_size;
    static EncodeTiledFn enc = nullptr;
    static void *xn, *kvT, *hbuf, *y2T, *flags, *stats;
    if (!enc) {
        void* fn = nullptr;
        cudaDriverEntryPointQueryResult qr;
        cudaGetDriverEntryPoint("cuTensorMapEncodeTiled", &fn, cudaEnableDefault, &qr);
        enc = (EncodeTiledFn)fn;
        cudaGetSymbolAddress(&xn, g_xn);
        cudaGetSymbolAddress(&kvT, g_kvT);
        cudaGetSymbolAddress(&hbuf, g_h);
        cudaGetSymbolAddress(&y2T, g_y2T);
        cudaGetSymbolAddress(&flags, g_flags);
        cudaGetSymbolAddress(&stats, g_stats);
        cudaFuncSetAttribute(h3_kernel, cudaFuncAttributeMaxDynamicSharedMemorySize, SMEM_BYTES);
    }
    Params p;
    const bf16* q = (const bf16*)d_in[0];
    p.q = q; p.k = (const bf16*)d_in[1]; p.v = (const bf16*)d_in[2];
    p.shift_k = (const bf16*)d_in[3]; p.ssm_k = (const bf16*)d_in[4]; p.ssm_D = (const bf16*)d_in[5];
    const bf16* wg = (const bf16*)d_in[7];
    const bf16* wu = (const bf16*)d_in[8];
    const bf16* wd = (const bf16*)d_in[9];
    p.xn = (bf16*)xn; p.kvT = (bf16*)kvT; p.y2T = (bf16*)y2T; p.flags = (unsigned*)flags; p.stats = (uint2*)stats;
    map2d(enc, &p.tmXn128, xn, D, S, 128);
    map2d(enc, &p.tmXn64, xn, D, S, 64);
    map3d(enc, &p.tmWg2, wg, F, D, 2);
    map3d(enc, &p.tmWu2, wu, F, D, 2);
    map3d(enc, &p.tmWg1, wg, F, D, 1);
    map3d(enc, &p.tmWu1, wu, F, D, 1);
    map2d(enc, &p.tmH64, hbuf, F, S, 64);
    map3d(enc, &p.tmWd, wd, D, F, 2);
    map2d(enc, &p.tmX128, q, D, S, 128);
    map2d(enc, &p.tmY2T, y2T, S, D, 128);
    map2d(enc, &p.tmOut64, d_out, D, S, 64);
    {
        const uint64_t d[2] = {D, S}, st[1] = {D * 2};
        const uint32_t bk[2] = {128, 67}, bv[2] = {128, 64};
        make_map(enc, &p.tmK, p.k, 2, d, st, bk, CU_TENSOR_MAP_SWIZZLE_NONE);
        make_map(enc, &p.tmV, p.v, 2, d, st, bv, CU_TENSOR_MAP_SWIZZLE_NONE);
    }
    map2d(enc, &p.tmKvT, kvT, S, D, 128);

    cudaLaunchConfig_t cfg = {};
    cfg.gridDim = dim3(NCTA + 4);
    cfg.blockDim = dim3(384);
    cfg.dynamicSmemBytes = SMEM_BYTES;
    cfg.stream = cudaStreamPerThread;
    cudaLaunchAttribute at[1];
    at[0].id = cudaLaunchAttributeClusterDimension;
    at[0].val.clusterDim.x = 2; at[0].val.clusterDim.y = 1; at[0].val.clusterDim.z = 1;
    cfg.attrs = at; cfg.numAttrs = 1;
    cudaLaunchKernelEx(&cfg, h3_kernel, p);
}
```

```cpp
#include <cuda_runtime.h>
#include <cuda_bf16.h>
#include <cuda.h>
#include <stdint.h>
#include <stdio.h>

namespace h3 {

typedef __nv_bfloat16 bf16;

constexpr int S = 2048;
constexpr int D = 1024;
constexpr int F = 3584;
constexpr int NCTA = 128;

__device__ __align__(1024) bf16 g_xn[S * D];
__device__ __align__(1024) bf16 g_kvT[D * S];
__device__ __align__(1024) bf16 g_h[S * F];
__device__ __align__(1024) bf16 g_y2T[D * S];
__device__ __align__(1024) uint2 g_stats[S];
constexpr int FLAG_STRIDE = 32;
constexpr int FL_XN = 0, FL_H = 16, FL_Y = 32, FL_KV = 40, FL_DONE = 41, FL_H2 = 42, FL_COUNT = 58;
__device__ __align__(1024) unsigned g_flags[FL_COUNT * FLAG_STRIDE];

struct alignas(64) Params {
    CUtensorMap tmXn128;
    CUtensorMap tmXn64;
    CUtensorMap tmWg2;
    CUtensorMap tmWu2;
    CUtensorMap tmWg1;
    CUtensorMap tmWu1;
    CUtensorMap tmH64;
    CUtensorMap tmWd;
    CUtensorMap tmX128;
    CUtensorMap tmY2T;
    CUtensorMap tmOut64;
    CUtensorMap tmK;
    CUtensorMap tmV;
    CUtensorMap tmKvT;
    const bf16* q; const bf16* k; const bf16* v; const bf16* shift_k; const bf16* ssm_k; const bf16* ssm_D;
    bf16* xn; bf16* kvT; bf16* y2T; uint2* stats;
    unsigned* flags;
};

constexpr uint32_t RING_BYTES = 196608;
constexpr uint32_t A_STAGE = 49152, B_STAGE = 32768;
constexpr uint32_t OFF_STG = RING_BYTES + 1024;
constexpr uint32_t OFF_BAR = OFF_STG + 32768;
constexpr uint32_t BAR_FULLA = 0, BAR_EMPTYA = 32, BAR_FULLB = 96, BAR_EMPTYB = 144,
                   BAR_STGFULL = 200, BAR_STGEMPTY = 208, BAR_ALTFULL = 216, BAR_OPFULL = 232,
                   BAR_ALT2FULL = 240, OFF_STAT = 256;
constexpr uint32_t SMEM_BYTES = OFF_BAR + 512 + 1024;

constexpr int ST_H = 4, ST_U = 5, ST_C0 = 0, ST_C1 = 1, ST_ALT = 2, ST_ALT2 = 3;
constexpr uint32_t U_PITCH = 4096 + 128;

__device__ __forceinline__ uint32_t smem_u32(const void* p) { return (uint32_t)__cvta_generic_to_shared(p); }
__device__ __forceinline__ uint64_t make_desc(uint32_t addr, uint32_t lbo, uint32_t sbo) {
    uint64_t d = (uint64_t)((addr & 0x3FFFF) >> 4);
    d |= (uint64_t)((lbo & 0x3FFFF) >> 4) << 16;
    d |= (uint64_t)((sbo & 0x3FFFF) >> 4) << 32;
    d |= (uint64_t)1 << 62;
    return d;
}
__device__ __forceinline__ uint64_t make_desc_noswz(uint32_t addr, uint32_t lbo, uint32_t sbo) {
    return (uint64_t)((addr & 0x3FFFF) >> 4) | ((uint64_t)(lbo >> 4) << 16) | ((uint64_t)(sbo >> 4) << 32);
}
constexpr uint32_t WAIT_LIMIT = 1u << 27;
__device__ __forceinline__ void mbar_init(uint32_t bar, uint32_t count) { asm volatile("mbarrier.init.shared::cta.b64 [%0], %1;" :: "r"(bar), "r"(count) : "memory"); }
__device__ __forceinline__ void mbar_expect_tx(uint32_t bar, uint32_t bytes) { asm volatile("mbarrier.arrive.expect_tx.shared::cta.b64 _, [%0], %1;" :: "r"(bar), "r"(bytes) : "memory"); }
__device__ __forceinline__ void mbar_arrive(uint32_t bar) { asm volatile("mbarrier.arrive.shared::cta.b64 _, [%0];" :: "r"(bar) : "memory"); }
__device__ __forceinline__ void mbar_arrive_cta(uint32_t bar, uint32_t cta) {
    asm volatile("{\n.reg .b32 ra;\nmapa.shared::cluster.u32 ra, %0, %1;\nmbarrier.arrive.shared::cluster.b64 _, [ra];\n}" :: "r"(bar), "r"(cta) : "memory");
}
__device__ __forceinline__ uint32_t mbar_try(uint32_t bar, uint32_t parity) {
    uint32_t ok;
    asm volatile("{\n.reg .pred p;\nmbarrier.try_wait.parity.shared::cta.b64 p, [%1], %2;\nselp.u32 %0, 1, 0, p;\n}" : "=r"(ok) : "r"(bar), "r"(parity) : "memory");
    return ok;
}
__device__ __forceinline__ void mbar_wait(uint32_t bar, uint32_t parity) {
    if (!mbar_try(bar, parity)) {
        const uint32_t t0 = (uint32_t)clock();
        while (!mbar_try(bar, parity) && (uint32_t)clock() - t0 < WAIT_LIMIT) {}
    }
}
__device__ __forceinline__ void mbar_wait_idle(uint32_t bar, uint32_t parity) {
    const uint32_t t0 = (uint32_t)clock();
    while (!mbar_try(bar, parity) && (uint32_t)clock() - t0 < WAIT_LIMIT) {
        __nanosleep(256);
    }
}
__device__ __forceinline__ void flag_wait(const unsigned* f, unsigned target) {
    const uint32_t t0 = (uint32_t)clock();
    unsigned v;
    do {
        asm volatile("ld.acquire.gpu.global.u32 %0, [%1];" : "=r"(v) : "l"(f) : "memory");
    } while (v < target && (uint32_t)clock() - t0 < WAIT_LIMIT);
}
__device__ __forceinline__ void flag_add_after_bulk(unsigned* f) {
    asm volatile("red.relaxed.gpu.global.add.u32 [%0], 1;" :: "l"(f) : "memory");
}
__device__ __forceinline__ void cluster_arrive() { asm volatile("barrier.cluster.arrive.relaxed;" ::: "memory"); }
__device__ __forceinline__ void cluster_wait() { asm volatile("barrier.cluster.wait.acquire;" ::: "memory"); }
__device__ __forceinline__ void tma_2d(uint32_t dst, const CUtensorMap* m, int c0, int c1, uint32_t bar) {
    asm volatile("cp.async.bulk.tensor.2d.shared::cluster.global.mbarrier::complete_tx::bytes [%0], [%1, {%3, %4}], [%2];"
        :: "r"(dst), "l"(m), "r"(bar), "r"(c0), "r"(c1) : "memory");
}
__device__ __forceinline__ void tma_2d_mc(uint32_t dst, const CUtensorMap* m, int c0, int c1, uint32_t bar) {
    asm volatile("cp.async.bulk.tensor.2d.shared::cluster.global.mbarrier::complete_tx::bytes.multicast::cluster [%0], [%1, {%3, %4}], [%2], %5;"
        :: "r"(dst), "l"(m), "r"(bar), "r"(c0), "r"(c1), "h"((uint16_t)3) : "memory");
}
__device__ __forceinline__ void tma_3d(uint32_t dst, const CUtensorMap* m, int c0, int c1, int c2, uint32_t bar) {
    asm volatile("cp.async.bulk.tensor.3d.shared::cluster.global.mbarrier::complete_tx::bytes [%0], [%1, {%3, %4, %5}], [%2];"
        :: "r"(dst), "l"(m), "r"(bar), "r"(c0), "r"(c1), "r"(c2) : "memory");
}
__device__ __forceinline__ uint64_t policy_evict_first() {
    uint64_t pol; asm volatile("createpolicy.fractional.L2::evict_first.b64 %0, 1.0;" : "=l"(pol)); return pol;
}
__device__ __forceinline__ void tma_3d_h(uint32_t dst, const CUtensorMap* m, int c0, int c1, int c2, uint32_t bar, uint64_t pol) {
    asm volatile("cp.async.bulk.tensor.3d.shared::cluster.global.mbarrier::complete_tx::bytes.L2::cache_hint [%0], [%1, {%3, %4, %5}], [%2], %6;"
        :: "r"(dst), "l"(m), "r"(bar), "r"(c0), "r"(c1), "r"(c2), "l"(pol) : "memory");
}
__device__ __forceinline__ void tma_2d_h(uint32_t dst, const CUtensorMap* m, int c0, int c1, uint32_t bar, uint64_t pol) {
    asm volatile("cp.async.bulk.tensor.2d.shared::cluster.global.mbarrier::complete_tx::bytes.L2::cache_hint [%0], [%1, {%3, %4}], [%2], %5;"
        :: "r"(dst), "l"(m), "r"(bar), "r"(c0), "r"(c1), "l"(pol) : "memory");
}
__device__ __forceinline__ void pf_bulk_h(const void* src, uint32_t bytes, uint64_t pol) {
    asm volatile("cp.async.bulk.prefetch.L2.global.L2::cache_hint [%0], %1, %2;" :: "l"(src), "r"(bytes), "l"(pol) : "memory");
}
__device__ __forceinline__ void tma_3d_mc_h(uint32_t dst, const CUtensorMap* m, int c0, int c1, int c2, uint32_t bar, uint64_t pol) {
    asm volatile("cp.async.bulk.tensor.3d.shared::cluster.global.mbarrier::complete_tx::bytes.multicast::cluster.L2::cache_hint [%0], [%1, {%3, %4, %5}], [%2], %6, %7;"
        :: "r"(dst), "l"(m), "r"(bar), "r"(c0), "r"(c1), "r"(c2), "h"((uint16_t)3), "l"(pol) : "memory");
}
__device__ __forceinline__ void bulk_g2s_h(uint32_t dst, const void* src, uint32_t bytes, uint32_t bar, uint64_t pol) {
    asm volatile("cp.async.bulk.shared::cluster.global.mbarrier::complete_tx::bytes.L2::cache_hint [%0], [%1], %2, [%3], %4;"
        :: "r"(dst), "l"(src), "r"(bytes), "r"(bar), "l"(pol) : "memory");
}
__device__ __forceinline__ void bulk_s2g(void* dst, uint32_t src, uint32_t bytes) {
    asm volatile("cp.async.bulk.global.shared::cta.bulk_group [%0], [%1], %2;" :: "l"(dst), "r"(src), "r"(bytes) : "memory");
}
__device__ __forceinline__ void tma_store_2d(const CUtensorMap* m, uint32_t src, int c0, int c1) {
    asm volatile("cp.async.bulk.tensor.2d.global.shared::cta.bulk_group [%0, {%2, %3}], [%1];"
        :: "l"(m), "r"(src), "r"(c0), "r"(c1) : "memory");
}
__device__ __forceinline__ void pf_2d(const CUtensorMap* m, int c0, int c1) {
    asm volatile("cp.async.bulk.prefetch.tensor.2d.L2.global.tile [%0, {%1, %2}];" :: "l"(m), "r"(c0), "r"(c1) : "memory");
}
__device__ __forceinline__ void pf_bulk(const void* src, uint32_t bytes) {
    asm volatile("cp.async.bulk.prefetch.L2.global [%0], %1;" :: "l"(src), "r"(bytes) : "memory");
}
__device__ __forceinline__ void bulk_commit() { asm volatile("cp.async.bulk.commit_group;" ::: "memory"); }
__device__ __forceinline__ void bulk_wait_read() { asm volatile("cp.async.bulk.wait_group.read 0;" ::: "memory"); }
__device__ __forceinline__ void bulk_wait_all() { asm volatile("cp.async.bulk.wait_group 0;" ::: "memory"); }
__device__ __forceinline__ void fence_async_smem() { asm volatile("fence.proxy.async.shared::cta;" ::: "memory"); }
__device__ __forceinline__ void bar_sync(int id, int n) { asm volatile("bar.sync %0, %1;" :: "r"(id), "r"(n) : "memory"); }
__device__ __forceinline__ void bar_arrive(int id, int n) { asm volatile("bar.arrive %0, %1;" :: "r"(id), "r"(n) : "memory"); }
__device__ __forceinline__ void cluster_wait_end() { asm volatile("barrier.cluster.wait;" ::: "memory"); }
__device__ __forceinline__ void cluster_sync() {
    asm volatile("barrier.cluster.arrive.relaxed.aligned;" ::: "memory");
    asm volatile("barrier.cluster.wait.aligned;" ::: "memory");
}
__device__ __forceinline__ void wg_fence() { asm volatile("wgmma.fence.sync.aligned;" ::: "memory"); }
__device__ __forceinline__ void wg_commit() { asm volatile("wgmma.commit_group.sync.aligned;" ::: "memory"); }
template <int N> __device__ __forceinline__ void wg_wait() { asm volatile("wgmma.wait_group.sync.aligned %0;" :: "n"(N) : "memory"); }

#define H3_R4(b)  "+f"(d[b+0]), "+f"(d[b+1]), "+f"(d[b+2]), "+f"(d[b+3])
#define H3_R8(b)  H3_R4(b), H3_R4(b+4)
#define H3_R16(b) H3_R8(b), H3_R8(b+8)
#define H3_R32(b) H3_R16(b), H3_R16(b+16)
#define H3_R64(b) H3_R32(b), H3_R32(b+32)

__device__ __forceinline__ void wgmma_256(float (&d)[128], uint64_t a, uint64_t b, int scale_d) {
    asm volatile("{\n.reg .pred p;\nsetp.ne.b32 p, %130, 0;\n"
    "wgmma.mma_async.sync.aligned.m64n256k16.f32.bf16.bf16 "
    "{%0,%1,%2,%3,%4,%5,%6,%7,%8,%9,%10,%11,%12,%13,%14,%15,"
    "%16,%17,%18,%19,%20,%21,%22,%23,%24,%25,%26,%27,%28,%29,%30,%31,"
    "%32,%33,%34,%35,%36,%37,%38,%39,%40,%41,%42,%43,%44,%45,%46,%47,"
    "%48,%49,%50,%51,%52,%53,%54,%55,%56,%57,%58,%59,%60,%61,%62,%63,"
    "%64,%65,%66,%67,%68,%69,%70,%71,%72,%73,%74,%75,%76,%77,%78,%79,"
    "%80,%81,%82,%83,%84,%85,%86,%87,%88,%89,%90,%91,%92,%93,%94,%95,"
    "%96,%97,%98,%99,%100,%101,%102,%103,%104,%105,%106,%107,%108,%109,%110,%111,"
    "%112,%113,%114,%115,%116,%117,%118,%119,%120,%121,%122,%123,%124,%125,%126,%127},"
    "%128, %129, p, 1, 1, 0, 1;\n}\n"
    : H3_R64(0), H3_R64(64)
    : "l"(a), "l"(b), "r"(scale_d));
}
__device__ __forceinline__ void wgmma_128(float (&d)[64], uint64_t a, uint64_t b, int scale_d) {
    asm volatile("{\n.reg .pred p;\nsetp.ne.b32 p, %66, 0;\n"
    "wgmma.mma_async.sync.aligned.m64n128k16.f32.bf16.bf16 "
    "{%0,%1,%2,%3,%4,%5,%6,%7,%8,%9,%10,%11,%12,%13,%14,%15,"
    "%16,%17,%18,%19,%20,%21,%22,%23,%24,%25,%26,%27,%28,%29,%30,%31,"
    "%32,%33,%34,%35,%36,%37,%38,%39,%40,%41,%42,%43,%44,%45,%46,%47,"
    "%48,%49,%50,%51,%52,%53,%54,%55,%56,%57,%58,%59,%60,%61,%62,%63},"
    "%64, %65, p, 1, 1, 0, 1;\n}\n"
    : H3_R64(0)
    : "l"(a), "l"(b), "r"(scale_d));
}
__device__ __forceinline__ void ldsm_x4(uint32_t addr, uint32_t& r0, uint32_t& r1, uint32_t& r2, uint32_t& r3) {
    asm volatile("ldmatrix.sync.aligned.m8n8.x4.shared.b16 {%0,%1,%2,%3}, [%4];" : "=r"(r0), "=r"(r1), "=r"(r2), "=r"(r3) : "r"(addr) : "memory");
}
__device__ __forceinline__ void ldsm_x4_t(uint32_t addr, uint32_t& r0, uint32_t& r1, uint32_t& r2, uint32_t& r3) {
    asm volatile("ldmatrix.sync.aligned.m8n8.x4.trans.shared.b16 {%0,%1,%2,%3}, [%4];" : "=r"(r0), "=r"(r1), "=r"(r2), "=r"(r3) : "r"(addr) : "memory");
}
__device__ __forceinline__ void stsm_x4(uint32_t addr, uint32_t r0, uint32_t r1, uint32_t r2, uint32_t r3) {
    asm volatile("stmatrix.sync.aligned.m8n8.x4.shared.b16 [%0], {%1,%2,%3,%4};" :: "r"(addr), "r"(r0), "r"(r1), "r"(r2), "r"(r3) : "memory");
}
template <int OFF> __device__ __forceinline__ uint32_t lds32_o(uint32_t addr) { uint32_t v; asm volatile("ld.shared.b32 %0, [%1+%2];" : "=r"(v) : "r"(addr), "n"(OFF) : "memory"); return v; }
__device__ __forceinline__ uint32_t lds32(uint32_t addr) { uint32_t v; asm volatile("ld.shared.b32 %0, [%1];" : "=r"(v) : "r"(addr) : "memory"); return v; }
__device__ __forceinline__ uint4 lds128(uint32_t addr) { uint4 v; asm volatile("ld.shared.v4.b32 {%0,%1,%2,%3}, [%4];" : "=r"(v.x), "=r"(v.y), "=r"(v.z), "=r"(v.w) : "r"(addr) : "memory"); return v; }
__device__ __forceinline__ void sts128(uint32_t addr, uint32_t a, uint32_t b, uint32_t c, uint32_t d) { asm volatile("st.shared.v4.b32 [%0], {%1,%2,%3,%4};" :: "r"(addr), "r"(a), "r"(b), "r"(c), "r"(d) : "memory"); }

__device__ __forceinline__ uint32_t bf2_mul(uint32_t a, uint32_t b) { uint32_t r; asm("mul.rn.bf16x2 %0, %1, %2;" : "=r"(r) : "r"(a), "r"(b)); return r; }
__device__ __forceinline__ uint32_t bf2_add(uint32_t a, uint32_t b) { uint32_t r; asm("add.rn.bf16x2 %0, %1, %2;" : "=r"(r) : "r"(a), "r"(b)); return r; }
__device__ __forceinline__ uint32_t bf2_sub(uint32_t a, uint32_t b) { uint32_t r; asm("sub.rn.bf16x2 %0, %1, %2;" : "=r"(r) : "r"(a), "r"(b)); return r; }
__device__ __forceinline__ uint32_t pack_bf2(float lo, float hi) { uint32_t r; asm("cvt.rn.bf16x2.f32 %0, %1, %2;" : "=r"(r) : "f"(hi), "f"(lo)); return r; }
__device__ __forceinline__ float bf_lo(uint32_t v) { return __uint_as_float(v << 16); }
__device__ __forceinline__ float bf_hi(uint32_t v) { return __uint_as_float(v & 0xFFFF0000u); }
__device__ __forceinline__ float silu_f(float x) {
    float e, r;
    asm("ex2.approx.ftz.f32 %0, %1;" : "=f"(e) : "f"(x * -1.4426950408889634f));
    asm("rcp.approx.ftz.f32 %0, %1;" : "=f"(r) : "f"(1.0f + e));
    return x * r;
}
__device__ __forceinline__ uint32_t silu_bf2(uint32_t v) { return pack_bf2(silu_f(bf_lo(v)), silu_f(bf_hi(v))); }


template <int I>
__device__ __forceinline__ void stage_piece(const uint32_t (&pg)[32], const uint32_t (&pu)[32], uint32_t stg_lane, uint32_t lrow7, uint32_t lgrp) {
    const uint32_t addr = stg_lane + (((2 * (I & 3) + lgrp) ^ lrow7) << 4);
    stsm_x4(addr, pg[4 * I], pg[4 * I + 1], pg[4 * I + 2], pg[4 * I + 3]);
    stsm_x4(addr + 8192, pu[4 * I], pu[4 * I + 1], pu[4 * I + 2], pu[4 * I + 3]);
}
__device__ __forceinline__ void stage_piece_dyn(int i, const uint32_t (&pg)[32], const uint32_t (&pu)[32], uint32_t stg_lane, uint32_t lrow7, uint32_t lgrp) {
    switch (i) {
        case 0: stage_piece<0>(pg, pu, stg_lane, lrow7, lgrp); break;
        case 1: stage_piece<1>(pg, pu, stg_lane, lrow7, lgrp); break;
        case 2: stage_piece<2>(pg, pu, stg_lane, lrow7, lgrp); break;
        case 3: stage_piece<3>(pg, pu, stg_lane, lrow7, lgrp); break;
        case 4: stage_piece<4>(pg, pu, stg_lane, lrow7, lgrp); break;
        case 5: stage_piece<5>(pg, pu, stg_lane, lrow7, lgrp); break;
        case 6: stage_piece<6>(pg, pu, stg_lane, lrow7, lgrp); break;
        default: stage_piece<7>(pg, pu, stg_lane, lrow7, lgrp); break;
    }
}
__device__ __forceinline__ void wgmma_128_lo(float (&d)[128], uint64_t a, uint64_t b, int scale_d) {
    asm volatile("{\n.reg .pred p;\nsetp.ne.b32 p, %66, 0;\n"
    "wgmma.mma_async.sync.aligned.m64n128k16.f32.bf16.bf16 "
    "{%0,%1,%2,%3,%4,%5,%6,%7,%8,%9,%10,%11,%12,%13,%14,%15,"
    "%16,%17,%18,%19,%20,%21,%22,%23,%24,%25,%26,%27,%28,%29,%30,%31,"
    "%32,%33,%34,%35,%36,%37,%38,%39,%40,%41,%42,%43,%44,%45,%46,%47,"
    "%48,%49,%50,%51,%52,%53,%54,%55,%56,%57,%58,%59,%60,%61,%62,%63},"
    "%64, %65, p, 1, 1, 0, 1;\n}\n"
    : H3_R64(0)
    : "l"(a), "l"(b), "r"(scale_d));
}

template <int N> __device__ __forceinline__ void wgmma_rs(float (&d)[128], const uint32_t (&a)[4], uint64_t b, int scale_d);
template <> __device__ __forceinline__ void wgmma_rs<64>(float (&d)[128], const uint32_t (&a)[4], uint64_t b, int scale_d) {
    asm volatile("{\n.reg .pred p;\nsetp.ne.b32 p, %37, 0;\nwgmma.mma_async.sync.aligned.m64n64k16.f32.bf16.bf16 {%0,%1,%2,%3,%4,%5,%6,%7,%8,%9,%10,%11,%12,%13,%14,%15,%16,%17,%18,%19,%20,%21,%22,%23,%24,%25,%26,%27,%28,%29,%30,%31}, {%32,%33,%34,%35}, %36, p, 1, 1, 0;\n}\n"
        : "+f"(d[0]), "+f"(d[1]), "+f"(d[2]), "+f"(d[3]), "+f"(d[4]), "+f"(d[5]), "+f"(d[6]), "+f"(d[7]), "+f"(d[8]), "+f"(d[9]), "+f"(d[10]), "+f"(d[11]), "+f"(d[12]), "+f"(d[13]), "+f"(d[14]), "+f"(d[15]), "+f"(d[16]), "+f"(d[17]), "+f"(d[18]), "+f"(d[19]), "+f"(d[20]), "+f"(d[21]), "+f"(d[22]), "+f"(d[23]), "+f"(d[24]), "+f"(d[25]), "+f"(d[26]), "+f"(d[27]), "+f"(d[28]), "+f"(d[29]), "+f"(d[30]), "+f"(d[31])
        : "r"(a[0]), "r"(a[1]), "r"(a[2]), "r"(a[3]), "l"(b), "r"(scale_d));
}
template <> __device__ __forceinline__ void wgmma_rs<128>(float (&d)[128], const uint32_t (&a)[4], uint64_t b, int scale_d) {
    asm volatile("{\n.reg .pred p;\nsetp.ne.b32 p, %69, 0;\nwgmma.mma_async.sync.aligned.m64n128k16.f32.bf16.bf16 {%0,%1,%2,%3,%4,%5,%6,%7,%8,%9,%10,%11,%12,%13,%14,%15,%16,%17,%18,%19,%20,%21,%22,%23,%24,%25,%26,%27,%28,%29,%30,%31,%32,%33,%34,%35,%36,%37,%38,%39,%40,%41,%42,%43,%44,%45,%46,%47,%48,%49,%50,%51,%52,%53,%54,%55,%56,%57,%58,%59,%60,%61,%62,%63}, {%64,%65,%66,%67}, %68, p, 1, 1, 0;\n}\n"
        : "+f"(d[0]), "+f"(d[1]), "+f"(d[2]), "+f"(d[3]), "+f"(d[4]), "+f"(d[5]), "+f"(d[6]), "+f"(d[7]), "+f"(d[8]), "+f"(d[9]), "+f"(d[10]), "+f"(d[11]), "+f"(d[12]), "+f"(d[13]), "+f"(d[14]), "+f"(d[15]), "+f"(d[16]), "+f"(d[17]), "+f"(d[18]), "+f"(d[19]), "+f"(d[20]), "+f"(d[21]), "+f"(d[22]), "+f"(d[23]), "+f"(d[24]), "+f"(d[25]), "+f"(d[26]), "+f"(d[27]), "+f"(d[28]), "+f"(d[29]), "+f"(d[30]), "+f"(d[31]), "+f"(d[32]), "+f"(d[33]), "+f"(d[34]), "+f"(d[35]), "+f"(d[36]), "+f"(d[37]), "+f"(d[38]), "+f"(d[39]), "+f"(d[40]), "+f"(d[41]), "+f"(d[42]), "+f"(d[43]), "+f"(d[44]), "+f"(d[45]), "+f"(d[46]), "+f"(d[47]), "+f"(d[48]), "+f"(d[49]), "+f"(d[50]), "+f"(d[51]), "+f"(d[52]), "+f"(d[53]), "+f"(d[54]), "+f"(d[55]), "+f"(d[56]), "+f"(d[57]), "+f"(d[58]), "+f"(d[59]), "+f"(d[60]), "+f"(d[61]), "+f"(d[62]), "+f"(d[63])
        : "r"(a[0]), "r"(a[1]), "r"(a[2]), "r"(a[3]), "l"(b), "r"(scale_d));
}
template <> __device__ __forceinline__ void wgmma_rs<192>(float (&d)[128], const uint32_t (&a)[4], uint64_t b, int scale_d) {
    asm volatile("{\n.reg .pred p;\nsetp.ne.b32 p, %101, 0;\nwgmma.mma_async.sync.aligned.m64n192k16.f32.bf16.bf16 {%0,%1,%2,%3,%4,%5,%6,%7,%8,%9,%10,%11,%12,%13,%14,%15,%16,%17,%18,%19,%20,%21,%22,%23,%24,%25,%26,%27,%28,%29,%30,%31,%32,%33,%34,%35,%36,%37,%38,%39,%40,%41,%42,%43,%44,%45,%46,%47,%48,%49,%50,%51,%52,%53,%54,%55,%56,%57,%58,%59,%60,%61,%62,%63,%64,%65,%66,%67,%68,%69,%70,%71,%72,%73,%74,%75,%76,%77,%78,%79,%80,%81,%82,%83,%84,%85,%86,%87,%88,%89,%90,%91,%92,%93,%94,%95}, {%96,%97,%98,%99}, %100, p, 1, 1, 0;\n}\n"
        : "+f"(d[0]), "+f"(d[1]), "+f"(d[2]), "+f"(d[3]), "+f"(d[4]), "+f"(d[5]), "+f"(d[6]), "+f"(d[7]), "+f"(d[8]), "+f"(d[9]), "+f"(d[10]), "+f"(d[11]), "+f"(d[12]), "+f"(d[13]), "+f"(d[14]), "+f"(d[15]), "+f"(d[16]), "+f"(d[17]), "+f"(d[18]), "+f"(d[19]), "+f"(d[20]), "+f"(d[21]), "+f"(d[22]), "+f"(d[23]), "+f"(d[24]), "+f"(d[25]), "+f"(d[26]), "+f"(d[27]), "+f"(d[28]), "+f"(d[29]), "+f"(d[30]), "+f"(d[31]), "+f"(d[32]), "+f"(d[33]), "+f"(d[34]), "+f"(d[35]), "+f"(d[36]), "+f"(d[37]), "+f"(d[38]), "+f"(d[39]), "+f"(d[40]), "+f"(d[41]), "+f"(d[42]), "+f"(d[43]), "+f"(d[44]), "+f"(d[45]), "+f"(d[46]), "+f"(d[47]), "+f"(d[48]), "+f"(d[49]), "+f"(d[50]), "+f"(d[51]), "+f"(d[52]), "+f"(d[53]), "+f"(d[54]), "+f"(d[55]), "+f"(d[56]), "+f"(d[57]), "+f"(d[58]), "+f"(d[59]), "+f"(d[60]), "+f"(d[61]), "+f"(d[62]), "+f"(d[63]), "+f"(d[64]), "+f"(d[65]), "+f"(d[66]), "+f"(d[67]), "+f"(d[68]), "+f"(d[69]), "+f"(d[70]), "+f"(d[71]), "+f"(d[72]), "+f"(d[73]), "+f"(d[74]), "+f"(d[75]), "+f"(d[76]), "+f"(d[77]), "+f"(d[78]), "+f"(d[79]), "+f"(d[80]), "+f"(d[81]), "+f"(d[82]), "+f"(d[83]), "+f"(d[84]), "+f"(d[85]), "+f"(d[86]), "+f"(d[87]), "+f"(d[88]), "+f"(d[89]), "+f"(d[90]), "+f"(d[91]), "+f"(d[92]), "+f"(d[93]), "+f"(d[94]), "+f"(d[95])
        : "r"(a[0]), "r"(a[1]), "r"(a[2]), "r"(a[3]), "l"(b), "r"(scale_d));
}
template <> __device__ __forceinline__ void wgmma_rs<256>(float (&d)[128], const uint32_t (&a)[4], uint64_t b, int scale_d) {
    asm volatile("{\n.reg .pred p;\nsetp.ne.b32 p, %133, 0;\nwgmma.mma_async.sync.aligned.m64n256k16.f32.bf16.bf16 {%0,%1,%2,%3,%4,%5,%6,%7,%8,%9,%10,%11,%12,%13,%14,%15,%16,%17,%18,%19,%20,%21,%22,%23,%24,%25,%26,%27,%28,%29,%30,%31,%32,%33,%34,%35,%36,%37,%38,%39,%40,%41,%42,%43,%44,%45,%46,%47,%48,%49,%50,%51,%52,%53,%54,%55,%56,%57,%58,%59,%60,%61,%62,%63,%64,%65,%66,%67,%68,%69,%70,%71,%72,%73,%74,%75,%76,%77,%78,%79,%80,%81,%82,%83,%84,%85,%86,%87,%88,%89,%90,%91,%92,%93,%94,%95,%96,%97,%98,%99,%100,%101,%102,%103,%104,%105,%106,%107,%108,%109,%110,%111,%112,%113,%114,%115,%116,%117,%118,%119,%120,%121,%122,%123,%124,%125,%126,%127}, {%128,%129,%130,%131}, %132, p, 1, 1, 0;\n}\n"
        : "+f"(d[0]), "+f"(d[1]), "+f"(d[2]), "+f"(d[3]), "+f"(d[4]), "+f"(d[5]), "+f"(d[6]), "+f"(d[7]), "+f"(d[8]), "+f"(d[9]), "+f"(d[10]), "+f"(d[11]), "+f"(d[12]), "+f"(d[13]), "+f"(d[14]), "+f"(d[15]), "+f"(d[16]), "+f"(d[17]), "+f"(d[18]), "+f"(d[19]), "+f"(d[20]), "+f"(d[21]), "+f"(d[22]), "+f"(d[23]), "+f"(d[24]), "+f"(d[25]), "+f"(d[26]), "+f"(d[27]), "+f"(d[28]), "+f"(d[29]), "+f"(d[30]), "+f"(d[31]), "+f"(d[32]), "+f"(d[33]), "+f"(d[34]), "+f"(d[35]), "+f"(d[36]), "+f"(d[37]), "+f"(d[38]), "+f"(d[39]), "+f"(d[40]), "+f"(d[41]), "+f"(d[42]), "+f"(d[43]), "+f"(d[44]), "+f"(d[45]), "+f"(d[46]), "+f"(d[47]), "+f"(d[48]), "+f"(d[49]), "+f"(d[50]), "+f"(d[51]), "+f"(d[52]), "+f"(d[53]), "+f"(d[54]), "+f"(d[55]), "+f"(d[56]), "+f"(d[57]), "+f"(d[58]), "+f"(d[59]), "+f"(d[60]), "+f"(d[61]), "+f"(d[62]), "+f"(d[63]), "+f"(d[64]), "+f"(d[65]), "+f"(d[66]), "+f"(d[67]), "+f"(d[68]), "+f"(d[69]), "+f"(d[70]), "+f"(d[71]), "+f"(d[72]), "+f"(d[73]), "+f"(d[74]), "+f"(d[75]), "+f"(d[76]), "+f"(d[77]), "+f"(d[78]), "+f"(d[79]), "+f"(d[80]), "+f"(d[81]), "+f"(d[82]), "+f"(d[83]), "+f"(d[84]), "+f"(d[85]), "+f"(d[86]), "+f"(d[87]), "+f"(d[88]), "+f"(d[89]), "+f"(d[90]), "+f"(d[91]), "+f"(d[92]), "+f"(d[93]), "+f"(d[94]), "+f"(d[95]), "+f"(d[96]), "+f"(d[97]), "+f"(d[98]), "+f"(d[99]), "+f"(d[100]), "+f"(d[101]), "+f"(d[102]), "+f"(d[103]), "+f"(d[104]), "+f"(d[105]), "+f"(d[106]), "+f"(d[107]), "+f"(d[108]), "+f"(d[109]), "+f"(d[110]), "+f"(d[111]), "+f"(d[112]), "+f"(d[113]), "+f"(d[114]), "+f"(d[115]), "+f"(d[116]), "+f"(d[117]), "+f"(d[118]), "+f"(d[119]), "+f"(d[120]), "+f"(d[121]), "+f"(d[122]), "+f"(d[123]), "+f"(d[124]), "+f"(d[125]), "+f"(d[126]), "+f"(d[127])
        : "r"(a[0]), "r"(a[1]), "r"(a[2]), "r"(a[3]), "l"(b), "r"(scale_d));
}

template <int I> __device__ __forceinline__ void conv_load_a(uint32_t (&a)[16][4], const uint32_t (&hx)[8]) {
    constexpr int IP = I >> 2, SG = I & 3;
    a[I][0] = lds32_o<-1024 * IP>(hx[2 * SG]); a[I][1] = lds32_o<-1024 * IP - 512>(hx[2 * SG]);
    a[I][2] = lds32_o<-1024 * IP>(hx[2 * SG + 1]); a[I][3] = lds32_o<-1024 * IP - 512>(hx[2 * SG + 1]);
    if constexpr (I < 15) conv_load_a<I + 1>(a, hx);
}
template <int I> __device__ __forceinline__ void conv_issue(float (&acc)[128], const uint32_t (&a)[16][4], uint64_t db) {
    wgmma_rs<256 - 64 * (I >> 2)>(acc, a[I], db + 64 * (I >> 2) + 2 * (I & 3), I != 0);
    if constexpr (I < 15) conv_issue<I + 1>(acc, a, db);
}
__device__ __forceinline__ void conv_frag_addr(uint32_t (&hx)[8], uint32_t copy_base, int w0, uint32_t xb) {
#pragma unroll
    for (int i = 0; i < 8; i++) { const uint32_t W = (uint32_t)(w0 - 4 * i); hx[i] = copy_base + ((W ^ (((W >> 5) & 3u) << 2) ^ xb) << 2); }
}

__device__ __forceinline__ void kv_cta(const Params& p, uint32_t sb, int j) {
    constexpr uint32_t IN_BYTES = 17408 + 16384, OFF_V = 17408;
    constexpr uint32_t OFF_OUT = 4 * IN_BYTES, OFF_TAPS = OFF_OUT + 4 * 16384;
    constexpr uint32_t B_INF = 0, B_INE = 32, B_OUTF = 64, B_OUTE = 96;
    const uint32_t bars = sb + OFF_BAR;
    const int tid = threadIdx.x, lane = tid & 31;
    if (tid == 0) {
        for (int s = 0; s < 4; s++) { mbar_init(bars + B_INF + 8 * s, 1); mbar_init(bars + B_INE + 8 * s, 8); mbar_init(bars + B_OUTF + 8 * s, 8); mbar_init(bars + B_OUTE + 8 * s, 1); }
        asm volatile("fence.mbarrier_init.release.cluster;" ::: "memory");
    }
    for (int i = tid; i < 512; i += 384) { const uint4 t = __ldg(reinterpret_cast<const uint4*>(p.shift_k) + i); sts128(sb + OFF_TAPS + i * 16, t.x, t.y, t.z, t.w); }
    __syncthreads();
    if (tid == 0) {
        const uint64_t pol = policy_evict_first();
#pragma unroll 1
        for (int i = 0; i < 64 + 3; i++) {
            if (i < 64) {
                const int bf = i & 3, t0 = j * 512 + (i >> 3) * 64, c0 = (i & 7) * 128;
                if (i >= 4) mbar_wait(bars + B_INE + 8 * bf, ((i >> 2) - 1) & 1);
                mbar_expect_tx(bars + B_INF + 8 * bf, 67 * 256 + 64 * 256);
                tma_2d_h(sb + bf * IN_BYTES, &p.tmK, c0, t0 - 3, bars + B_INF + 8 * bf, pol);
                tma_2d_h(sb + bf * IN_BYTES + OFF_V, &p.tmV, c0, t0, bars + B_INF + 8 * bf, pol);
            }
            if (i >= 3) {
                const int o = i - 3, bf = o & 3;
                mbar_wait(bars + B_OUTF + 8 * bf, (o >> 2) & 1);
                tma_store_2d(&p.tmKvT, sb + OFF_OUT + bf * 16384, 1984 - (j * 512 + (o >> 3) * 64), (o & 7) * 128);
                bulk_commit();
                asm volatile("cp.async.bulk.wait_group.read 1;" ::: "memory");
                if (o > 0) mbar_arrive(bars + B_OUTE + 8 * ((o - 1) & 3));
            }
        }
        bulk_wait_all();
        flag_add_after_bulk(p.flags + FL_KV * FLAG_STRIDE);
    } else if (tid >= 32) {
#pragma unroll 1
        for (int u = (tid >> 5) - 1; u < 512; u += 11) {
            const int i = u >> 3, bf = i & 3, o = u & 7;
            mbar_wait(bars + B_INF + 8 * bf, (i >> 2) & 1);
            if (i >= 4) mbar_wait(bars + B_OUTE + 8 * bf, ((i >> 2) - 1) & 1);
            const uint32_t out = sb + OFF_OUT + bf * 16384;
            const uint32_t odd = (lane >> 2) & 1, sel0 = odd ? 0x7632u : 0x5410u, sel1 = odd ? 0x5410u : 0x7632u;
            uint32_t kk[2][11], vv[2][8];
            uint4 sw[2];
#pragma unroll
            for (int it = 0; it < 2; it++) {
                const uint32_t rd = sb + bf * IN_BYTES + o * 8 * 256 + (it * 32 + lane) * 4;
#pragma unroll
                for (int r = 0; r < 11; r++) kk[it][r] = lds32(rd + r * 256);
#pragma unroll
                for (int r = 0; r < 8; r++) vv[it][r] = lds32(rd + OFF_V + r * 256);
                sw[it] = lds128(sb + OFF_TAPS + ((i & 7) * 64 + it * 32 + lane) * 16);
            }
#pragma unroll
            for (int it = 0; it < 2; it++) {
                const uint32_t w0 = __byte_perm(sw[it].x, sw[it].z, 0x5410), w1 = __byte_perm(sw[it].x, sw[it].z, 0x7632);
                const uint32_t w2 = __byte_perm(sw[it].y, sw[it].w, 0x5410), w3 = __byte_perm(sw[it].y, sw[it].w, 0x7632);
#pragma unroll
                for (int r = 0; r < 8; r++)
                    vv[it][r] = bf2_mul(bf2_add(bf2_add(bf2_add(bf2_mul(kk[it][r], w3), bf2_mul(kk[it][r + 1], w2)), bf2_mul(kk[it][r + 2], w1)), bf2_mul(kk[it][r + 3], w0)), vv[it][r]);
                const uint32_t r0 = 2 * (it * 32 + lane) + odd, r1 = r0 ^ 1;
                const uint32_t* v = vv[it];
                sts128(out + r0 * 128 + (((7 - o) ^ (r0 & 7)) << 4), __byte_perm(v[0], v[1], sel0), __byte_perm(v[2], v[3], sel0), __byte_perm(v[4], v[5], sel0), __byte_perm(v[6], v[7], sel0));
                sts128(out + r1 * 128 + (((7 - o) ^ (r1 & 7)) << 4), __byte_perm(v[0], v[1], sel1), __byte_perm(v[2], v[3], sel1), __byte_perm(v[4], v[5], sel1), __byte_perm(v[6], v[7], sel1));
            }
            fence_async_smem();
            __syncwarp();
            if (lane == 0) { mbar_arrive(bars + B_INE + 8 * bf); mbar_arrive(bars + B_OUTF + 8 * bf); }
        }
    }
}

__global__ void __launch_bounds__(384, 1) h3_kernel(const __grid_constant__ Params p) {
    extern __shared__ uint8_t smem_raw[];
    const uint32_t sb = (smem_u32(smem_raw) + 1023) & ~1023u;
    const uint32_t bars = sb + OFF_BAR;
    const int tid = threadIdx.x;
    const int wg = __shfl_sync(0xffffffffu, tid >> 7, 0);
    const int lane = tid & 31;
    const int cta = blockIdx.x;
    const int pair = cta >> 1;
    const uint32_t rank = cta & 1;

    if (cta >= NCTA) { kv_cta(p, sb, cta - NCTA); return; }

    uint32_t x[32];
    if (wg != 0) {
        const uint4* src = reinterpret_cast<const uint4*>(p.q + (size_t)(cta * 16 + ((tid >> 5) - 4) * 2 + (lane >> 4)) * D) + (lane & 15);
#pragma unroll
        for (int i = 0; i < 8; i++) { const uint4 t = __ldg(src + i * 16); x[4 * i] = t.x; x[4 * i + 1] = t.y; x[4 * i + 2] = t.z; x[4 * i + 3] = t.w; }
    }
    if (tid == 0) {
#pragma unroll 1
        for (int s = 0; s < 4; s++) { mbar_init(bars + BAR_FULLA + 8 * s, 1); mbar_init(bars + BAR_EMPTYA + 8 * s, 4); }
#pragma unroll 1
        for (int s = 0; s < 6; s++) { mbar_init(bars + BAR_FULLB + 8 * s, 1); mbar_init(bars + BAR_EMPTYB + 8 * s, 4); }
        mbar_init(bars + BAR_STGFULL, 8);
        mbar_init(bars + BAR_STGEMPTY, 1);
        mbar_init(bars + BAR_ALTFULL, 8);
        mbar_init(bars + BAR_ALT2FULL, 8);
        mbar_init(bars + BAR_OPFULL, 1);
        asm volatile("fence.mbarrier_init.release.cluster;" ::: "memory");
    }
    __syncthreads();
    cluster_arrive();

    const int grp = (pair < 4) ? 0 : (pair < 36) ? ((pair - 4) & 7) : 1 + (pair - 36) % 7;
    const int gj = (pair < 4) ? 4 + pair : (pair < 36) ? ((pair - 4) >> 3) : 4 + (pair - 36) / 7;
    const int m1 = 2 * grp + (int)rank, nb1 = gj;
    const int m2 = ((grp >> 2) << 3) | gj, pn = grp & 3;
    const int nh = 24 + pn;
    const int n2 = pn * 256 + (int)rank * 128;

    if (wg == 0) {
        asm volatile("setmaxnreg.dec.sync.aligned.u32 40;\n");
        const int warp = tid >> 5;
        if (warp == 0) {
            if (lane == 0) {
                const uint64_t pol = policy_evict_first();
                const int mrow1 = m1 * 128, mrow2 = m2 * 128 + (int)rank * 64, ngh = nh * 2 + (int)rank;
                const CUtensorMap* tmW = rank ? &p.tmWu2 : &p.tmWg2;
                const uint32_t woff = 16384 + rank * 16384;
                cluster_wait();
#pragma unroll 1
                for (int j = 0; j < 4; j++) {
                    const uint32_t full = bars + BAR_FULLA + 8 * j;
                    mbar_expect_tx(full, A_STAGE);
                    tma_3d_mc_h(sb + j * A_STAGE + woff, tmW, 0, j * 64, nb1 * 2, full, pol);
                }
                flag_wait(p.flags + (FL_XN + m1) * FLAG_STRIDE, 64);
#pragma unroll 1
                for (int j = 0; j < 4; j++) tma_2d(sb + j * A_STAGE, &p.tmXn128, j * 64, mrow1, bars + BAR_FULLA + 8 * j);
#pragma unroll 1
                for (int g = 4; g < 48; g++) {
                    const int st = g & 3, k0 = (g & 15) * 64, ng = ((g >> 4) * 8 + nb1) * 2;
                    const uint32_t full = bars + BAR_FULLA + 8 * st, a = sb + st * A_STAGE;
                    mbar_wait(bars + BAR_EMPTYA + 8 * st, ((g >> 2) - 1) & 1);
                    mbar_expect_tx(full, A_STAGE);
                    tma_2d(a, &p.tmXn128, k0, mrow1, full);
                    tma_3d_mc_h(a + woff, tmW, 0, k0, ng, full, pol);
                    if (g == 3 * ((cta & 31) >> 2) - 2) { pf_bulk_h(p.k + (size_t)cta * 16 * D, 32768, pol); pf_bulk_h(p.v + (size_t)cta * 16 * D, 32768, pol); }
                }
                flag_wait(p.flags + (FL_XN + m2) * FLAG_STRIDE, 64);
                pf_bulk_h(p.ssm_k + (size_t)cta * 8 * S, 32768, pol);
                int st = 0; uint32_t ph = 1;
#pragma unroll 1
                for (int e = 0; e < 16; e++) {
                    const uint32_t full = bars + BAR_FULLB + 8 * st, a = sb + st * B_STAGE;
                    if (e < 6) {
                        if (e != 2 && e != 5) mbar_wait(bars + BAR_EMPTYA + 8 * (e - (e >= 3)), 1);
                    } else {
                        mbar_wait(bars + BAR_EMPTYB + 8 * st, ph);
                    }
                    mbar_expect_tx(full, B_STAGE);
                    tma_2d_mc(a + rank * 8192, &p.tmXn64, e * 64, mrow2, full);
                    tma_3d_h(a + 16384, &p.tmWg1, 0, e * 64, ngh, full, pol);
                    tma_3d_h(a + 24576, &p.tmWu1, 0, e * 64, ngh, full, pol);
                    if (++st == 6) { st = 0; ph ^= 1; }
                }
                mbar_wait(bars + BAR_EMPTYB + 8 * ST_H, 1);
                mbar_expect_tx(bars + BAR_FULLB + 8 * ST_H, 32768);
                bulk_g2s_h(sb + ST_H * B_STAGE, p.ssm_k + (size_t)cta * 8 * S, 32768, bars + BAR_FULLB + 8 * ST_H, pol);
                unsigned kv_ready;
                asm volatile("ld.acquire.gpu.global.u32 %0, [%1];" : "=r"(kv_ready) : "l"(p.flags + FL_KV * FLAG_STRIDE) : "memory");
#pragma unroll 1
                for (int pass = 0; pass < 2; pass++) {
                    if ((pass == 0) == (kv_ready >= 4)) {
                        mbar_wait(bars + BAR_EMPTYB + 8 * ST_U, 1);
                        flag_wait(p.flags + FL_KV * FLAG_STRIDE, 4);
                        mbar_expect_tx(bars + BAR_FULLB + 8 * ST_U, 32768);
#pragma unroll 1
                        for (int ch = 0; ch < 8; ch++) bulk_g2s_h(sb + ST_U * B_STAGE + ch * U_PITCH, p.kvT + (size_t)(cta * 8 + ch) * S, 4096, bars + BAR_FULLB + 8 * ST_U, pol);
                    }
                    if (pass == 0) {
#pragma unroll 1
                        for (int c = 0; c < 4; c++) { mbar_wait(bars + BAR_EMPTYB + 8 * c, 0); mbar_arrive(bars + BAR_FULLB + 8 * c); }
                    }
                }
                flag_wait(p.flags + (FL_H + m2) * FLAG_STRIDE, 16);
                int i6 = 0; uint32_t rho = 0;
#pragma unroll 1
                for (int kb = 0; kb < 56; kb++) {
                    const int sg = (0x513024 >> (4 * i6)) & 15;
                    const uint32_t par = ((0x21u >> i6) & 1u) ^ rho;
                    const uint32_t full = bars + BAR_FULLB + 8 * sg, a = sb + sg * B_STAGE;
                    mbar_wait(bars + BAR_EMPTYB + 8 * sg, par ^ 1);
                    if (kb == 32) flag_wait(p.flags + (FL_H2 + m2) * FLAG_STRIDE, 16);
                    mbar_expect_tx(full, B_STAGE);
                    tma_2d_mc(a + rank * 8192, &p.tmH64, kb * 64, mrow2, full);
                    tma_3d(a + 16384, &p.tmWd, 0, kb * 64, n2 >> 6, full);
                    if (++i6 == 6) { i6 = 0; rho ^= 1; }
                }
                mbar_wait(bars + BAR_EMPTYB + 0, 0);
                mbar_expect_tx(bars + BAR_FULLB + 0, 32768);
                tma_2d(sb, &p.tmX128, n2, m2 * 128, bars + BAR_FULLB + 0);
                tma_2d(sb + 16384, &p.tmX128, n2 + 64, m2 * 128, bars + BAR_FULLB + 0);
                mbar_wait(bars + BAR_OPFULL, 0);
                unsigned old;
                asm volatile("atom.acq_rel.gpu.global.add.u32 %0, [%1], 1;" : "=r"(old) : "l"(p.flags + FL_DONE * FLAG_STRIDE) : "memory");
                if (old == NCTA - 1) {
#pragma unroll 1
                    for (int i = 0; i < FL_COUNT; i++) p.flags[i * FLAG_STRIDE] = 0;
                }
            } else {
                cluster_wait();
            }
        } else {
            cluster_wait();
            const int wt = tid - 32;
#pragma unroll 1
            for (int Ri = 0; Ri < 7; Ri++) {
                const int R = (Ri < 4) ? Ri : (Ri == 4) ? 6 : (Ri == 5) ? 4 : 5;
                const uint32_t buf = (R == 4) ? sb + ST_ALT2 * B_STAGE : (R == 6) ? sb + ST_ALT * B_STAGE : sb + OFF_STG;
                mbar_wait_idle(bars + ((R == 4) ? BAR_ALT2FULL : (R == 6) ? BAR_ALTFULL : BAR_STGFULL), (R < 4) ? (R & 1) : 0);
#pragma unroll 1
                for (int i0 = wt; i0 < 1024; i0 += 2 * 96) {
                    const int i1 = i0 + 96;
                    const uint32_t a0 = buf + (i0 >> 9) * 16384 + (i0 & 511) * 16;
                    const uint32_t a1 = (i1 < 1024) ? buf + (i1 >> 9) * 16384 + (i1 & 511) * 16 : a0;
                    uint4 g0 = lds128(a0), u0 = lds128(a0 + 8192), g1 = lds128(a1), u1 = lds128(a1 + 8192);
                    g0.x = bf2_mul(silu_bf2(g0.x), u0.x); g0.y = bf2_mul(silu_bf2(g0.y), u0.y); g0.z = bf2_mul(silu_bf2(g0.z), u0.z); g0.w = bf2_mul(silu_bf2(g0.w), u0.w);
                    g1.x = bf2_mul(silu_bf2(g1.x), u1.x); g1.y = bf2_mul(silu_bf2(g1.y), u1.y); g1.z = bf2_mul(silu_bf2(g1.z), u1.z); g1.w = bf2_mul(silu_bf2(g1.w), u1.w);
                    sts128(a0, g0.x, g0.y, g0.z, g0.w);
                    if (i1 < 1024) sts128(a1, g1.x, g1.y, g1.z, g1.w);
                }
                fence_async_smem();
                bar_sync(4, 96);
                if (wt == 0) {
                    const int mm = (R < 6) ? m1 : m2;
                    const int col = (R < 6) ? (8 * (R >> 1) + nb1) * 128 + (R & 1) * 64 : nh * 128 + (int)rank * 64;
                    tma_store_2d(&p.tmH64, buf, col, mm * 128);
                    tma_store_2d(&p.tmH64, buf + 16384, col, mm * 128 + 64);
                    bulk_commit();
                    bulk_wait_read();
                    if (R != 4 && R != 6) mbar_arrive(bars + BAR_STGEMPTY);
                    else {
                        const uint32_t eb = bars + BAR_EMPTYB + 8 * ((R == 4) ? ST_ALT2 : ST_ALT);
                        mbar_arrive_cta(eb, 0); mbar_arrive_cta(eb, 0); mbar_arrive_cta(eb, 1); mbar_arrive_cta(eb, 1);
                    }
                    if (R == 1 || R == 3 || R >= 5) {
                        bulk_wait_all();
                        flag_add_after_bulk(p.flags + ((R < 4 ? FL_H : FL_H2) + mm) * FLAG_STRIDE);
                    }
                }
            }
            if (wt == 0) {
                mbar_wait(bars + BAR_FULLB + 8 * 3, 0); mbar_wait(bars + BAR_FULLB + 8 * 3, 1); mbar_wait(bars + BAR_FULLB + 8 * 3, 0);
                pf_2d(&p.tmX128, n2, m2 * 128); pf_2d(&p.tmX128, n2 + 64, m2 * 128);
                flag_wait(p.flags + (FL_Y + (n2 >> 7)) * FLAG_STRIDE, 128);
                mbar_expect_tx(bars + BAR_OPFULL, 32768);
                tma_2d(sb + OFF_STG, &p.tmY2T, 1984 - m2 * 128, n2, bars + BAR_OPFULL);
                tma_2d(sb + OFF_STG + 16384, &p.tmY2T, 1920 - m2 * 128, n2, bars + BAR_OPFULL);
            }
        }
        __syncwarp();
        cluster_sync();
    } else {
        asm volatile("setmaxnreg.inc.sync.aligned.u32 232;\n");
        const int cw = wg - 1;
        const int w = (tid >> 5) & 3;
        const int wtid = tid & 127;

        {
            const int rl = (cw * 4 + w) * 2 + (lane >> 4);
            const uint32_t src = sb + OFF_STG + rl * 2048 + (lane & 15) * 16;
            float s0 = 0.f, s1 = 0.f, s2 = 0.f, s3 = 0.f;
#pragma unroll
            for (int i = 0; i < 32; i += 2) { s0 += bf_lo(x[i]); s1 += bf_hi(x[i]); s2 += bf_lo(x[i + 1]); s3 += bf_hi(x[i + 1]); }
            float s = (s0 + s1) + (s2 + s3);
#pragma unroll
            for (int o = 8; o > 0; o >>= 1) s += __shfl_xor_sync(0xffffffffu, s, o);
            const float mu = s * (1.0f / D);
            s0 = s1 = s2 = s3 = 0.f;
#pragma unroll
            for (int i = 0; i < 32; i += 2) {
                const float a = bf_lo(x[i]) - mu, b = bf_hi(x[i]) - mu, c = bf_lo(x[i + 1]) - mu, d = bf_hi(x[i + 1]) - mu;
                s0 = fmaf(a, a, s0); s1 = fmaf(b, b, s1); s2 = fmaf(c, c, s2); s3 = fmaf(d, d, s3);
            }
            float v = (s0 + s1) + (s2 + s3);
#pragma unroll
            for (int o = 8; o > 0; o >>= 1) v += __shfl_xor_sync(0xffffffffu, v, o);
            const uint32_t mu2 = pack_bf2(mu, mu);
            const float vb = bf_lo(pack_bf2(v * (1.0f / D), 0.f));
            const float ve = bf_lo(pack_bf2(vb + 1e-5f, 0.f));
            const float sd = bf_lo(pack_bf2(sqrtf(ve), 0.f));
            const float inv = __frcp_rn(sd);
#pragma unroll
            for (int i = 0; i < 8; i++) {
                uint32_t oo[4];
#pragma unroll
                for (int e = 0; e < 4; e++) { const uint32_t dd = bf2_sub(x[4 * i + e], mu2); oo[e] = pack_bf2(bf_lo(dd) * inv, bf_hi(dd) * inv); }
                sts128(src + i * 256, oo[0], oo[1], oo[2], oo[3]);
            }
            if ((lane & 15) == 0) asm volatile("st.shared.v2.b32 [%0], {%1, %2};" :: "r"(bars + OFF_STAT + rl * 8), "r"(mu2), "r"(__float_as_uint(inv)) : "memory");
            fence_async_smem();
            __syncwarp();
            if (lane == 0) {
                bulk_s2g(p.xn + (size_t)(cta * 16 + (cw * 4 + w) * 2) * D, sb + OFF_STG + (cw * 4 + w) * 4096, 4096);
                bulk_s2g(p.stats + cta * 16 + (cw * 4 + w) * 2, bars + OFF_STAT + (cw * 4 + w) * 16, 16);
                bulk_commit();
                bulk_wait_all();
                flag_add_after_bulk(p.flags + (FL_XN + (cta >> 3)) * FLAG_STRIDE);
            }
            bar_sync(3, 256);
        }
        cluster_wait();

        const uint32_t lrow = w * 16 + (lane & 7) + ((lane >> 3) & 1) * 8;
        const uint32_t lrow7 = lane & 7;
        const uint32_t lgrp = lane >> 4;
        const uint32_t stg_lane = sb + OFF_STG + cw * 16384 + lrow * 128;
        const uint64_t descA = make_desc(sb + cw * 8192, 16, 1024);
        const uint64_t descB = make_desc(sb + 16384, 8192, 1024);

        int st = 0; uint32_t ph = 0;
        uint32_t pg[32], pu[32], qg[16], qu[16];
        {
            float acc[128];
            int prev = 0;
#pragma unroll 1
            for (int g = 0; g < 64; g++) {
                const int kb = g & 15;
                if (g < 48) {
                    const int sa = g & 3;
                    mbar_wait(bars + BAR_FULLA + 8 * sa, (g >> 2) & 1);
                    const uint64_t da = descA + sa * (A_STAGE >> 4), db = descB + sa * (A_STAGE >> 4);
                    wg_fence();
                    wgmma_256(acc, da, db, kb != 0);
#pragma unroll
                    for (int k = 1; k < 4; k++) wgmma_256(acc, da + k * 2, db + k * 128, 1);
                    wg_commit();
                } else {
                    mbar_wait(bars + BAR_FULLB + 8 * st, ph);
                    const uint64_t da = descA + st * (B_STAGE >> 4), db = descB + st * (B_STAGE >> 4);
                    wg_fence();
                    wgmma_128_lo(acc, da, db, kb != 0);
#pragma unroll
                    for (int k = 1; k < 4; k++) wgmma_128_lo(acc, da + k * 2, db + k * 128, 1);
                    wg_commit();
                }
                wg_wait<1>();
                if (kb > 0) {
                    if (wtid < 2) mbar_arrive_cta(bars + ((g > 48) ? BAR_EMPTYB + 8 * prev : BAR_EMPTYA + 8 * ((g - 1) & 3)), wtid);
                }
                if (g >= 48) { prev = st; if (++st == 6) { st = 0; ph ^= 1; } }
                if (g >= 16 && g < 48) {
                    const int pc = (kb < 4) ? kb : ((kb >= 9 && kb < 13) ? kb - 5 : -1);
                    if (pc >= 0) {
                        if (pc == 0 && g >= 32) mbar_wait(bars + BAR_STGEMPTY, 1);
                        if (pc == 4) mbar_wait(bars + BAR_STGEMPTY, 0);
                        stage_piece_dyn(pc, pg, pu, stg_lane, lrow7, lgrp);
                        if ((pc & 3) == 3) { __syncwarp(); if (lane == 0) mbar_arrive(bars + BAR_STGFULL); }
                    }
                }
                if (kb == 15 && g < 48) {
                    wg_wait<0>();
                    if (wtid < 2) mbar_arrive_cta(bars + BAR_EMPTYA + 24, wtid);
#pragma unroll
                    for (int i = 0; i < 32; i++) { pg[i] = pack_bf2(acc[2 * i], acc[2 * i + 1]); pu[i] = pack_bf2(acc[64 + 2 * i], acc[64 + 2 * i + 1]); }
                }
            }
            wg_wait<0>();
            if (wtid < 2) mbar_arrive_cta(bars + BAR_EMPTYB + 8 * prev, wtid);
#pragma unroll
            for (int i = 0; i < 16; i++) { qg[i] = pack_bf2(acc[2 * i], acc[2 * i + 1]); qu[i] = pack_bf2(acc[32 + 2 * i], acc[32 + 2 * i + 1]); }
        }
        mbar_wait(bars + BAR_STGEMPTY, 1);
        stage_piece<4>(pg, pu, stg_lane, lrow7, lgrp); stage_piece<5>(pg, pu, stg_lane, lrow7, lgrp);
        stage_piece<6>(pg, pu, stg_lane, lrow7, lgrp); stage_piece<7>(pg, pu, stg_lane, lrow7, lgrp);
        __syncwarp(); if (lane == 0) mbar_arrive(bars + BAR_STGFULL);
        mbar_wait(bars + BAR_FULLB + 8 * ST_ALT, 1);
        {
            const uint32_t alt_lane = sb + ST_ALT * B_STAGE + cw * 16384 + lrow * 128;
#pragma unroll
            for (int i = 0; i < 4; i++) {
                const uint32_t addr = alt_lane + (((2 * i + lgrp) ^ lrow7) << 4);
                stsm_x4(addr, qg[4 * i], qg[4 * i + 1], qg[4 * i + 2], qg[4 * i + 3]);
                stsm_x4(addr + 8192, qu[4 * i], qu[4 * i + 1], qu[4 * i + 2], qu[4 * i + 3]);
            }
            __syncwarp(); if (lane == 0) mbar_arrive(bars + BAR_ALTFULL);
        }
        mbar_wait(bars + BAR_FULLB + 8 * ST_ALT2, 1);
        {
            const uint32_t alt_lane = sb + ST_ALT2 * B_STAGE + cw * 16384 + lrow * 128;
            stage_piece<0>(pg, pu, alt_lane, lrow7, lgrp); stage_piece<1>(pg, pu, alt_lane, lrow7, lgrp);
            stage_piece<2>(pg, pu, alt_lane, lrow7, lgrp); stage_piece<3>(pg, pu, alt_lane, lrow7, lgrp);
            __syncwarp(); if (lane == 0) mbar_arrive(bars + BAR_ALT2FULL);
        }
        {
            const int r = lane >> 2, c4 = lane & 3;
            mbar_wait(bars + BAR_FULLB + 8 * ST_H, 0);
            mbar_wait(bars + BAR_FULLB + 8 * ST_C0, 1);
            mbar_wait(bars + BAR_FULLB + 8 * ST_C1, 1);
            {
                const uint32_t sH = sb + ST_H * B_STAGE + (cw * 4 + w) * 4096;
                const uint32_t sA = sb + (w >> 1) * B_STAGE + ((w & 1) * 2 + cw) * 8192, sB = sA + 4096;
                uint4 hv[8]; uint32_t hp[8];
#pragma unroll
                for (int i = 0; i < 8; i++) {
                    const int Q = i * 32 + lane;
                    hv[i] = lds128(sH + (255 - Q) * 16);
                    hp[i] = lds32(sH + (254 - Q) * 16 + 12);
                }
                if (lane == 31) hp[7] = 0;
                const uint32_t qs = (uint32_t)(lane ^ ((lane >> 3) & 3)) * 16;
#pragma unroll
                for (int i = 0; i < 8; i++) {
                    const uint4 a = hv[i];
                    const uint32_t prev = hp[i];
                    sts128(sA + i * 512 + qs, __byte_perm(a.w, 0, 0x1032), __byte_perm(a.z, 0, 0x1032), __byte_perm(a.y, 0, 0x1032), __byte_perm(a.x, 0, 0x1032));
                    sts128(sB + i * 512 + (qs ^ 64), __byte_perm(a.w, a.z, 0x7610), __byte_perm(a.z, a.y, 0x7610), __byte_perm(a.y, a.x, 0x7610), __byte_perm(a.x, prev, 0x7610));
                }
            }
            mbar_wait(bars + BAR_FULLB + 8 * ST_U, 0);
            if (lane < 8) sts128(sb + ST_U * B_STAGE + (cw * 4 + w) * U_PITCH + 4096 + lane * 16, 0, 0, 0, 0);
            fence_async_smem();
            bar_sync(1 + cw, 128);
            if (wtid < 2) mbar_arrive_cta(bars + BAR_EMPTYB + 8 * ST_H, wtid);
            if (cw == 1) bar_arrive(5, 256);
            const uint32_t podd = r & 1, b0 = (r >> 1) & 1, b1 = r >> 2;
            const int w0 = 1023 - w + c4 - 32 * (r >> 1);
            const uint32_t cpy = podd ? 0u : 4096u, xb = podd ? 0u : 16u;
            const int y0 = 2 * w + (int)podd - 2 * c4;
            const uint32_t mask0 = (r >> 1) ? 0xFFFFFFFFu : ((y0 >= 0 ? 0x0000FFFFu : 0u) | (y0 >= 1 ? 0xFFFF0000u : 0u));
            uint32_t a[16][4];
            {
                uint32_t hx[8];
                conv_frag_addr(hx, sb + cw * 8192 + cpy, w0, xb);
                conv_load_a<0>(a, hx);
                a[0][0] &= mask0;
            }
            const uint2 dq = __ldg(reinterpret_cast<const uint2*>(p.ssm_D + cta * 8 + cw * 4));
            auto conv_finish = [&](int cp) {
                const uint32_t sA = sb + (cp >> 1) * B_STAGE + ((cp & 1) * 2 + cw) * 8192;
                const uint32_t sU = sb + ST_U * B_STAGE + (cw * 4 + cp) * U_PITCH;
                const uint32_t dw = (cp & 2) ? dq.y : dq.x;
                const uint32_t d2 = __byte_perm(dw, 0, (cp & 1) ? 0x3232 : 0x1010);
#pragma unroll
                for (int i = 0; i < 2; i++) {
                    const uint32_t beta = 64 * w + 32 * i + lane;
                    const uint4 kv = lds128(sU + beta * 16);
                    const uint32_t y0w = lds32_o<0>(sA + beta * 4), y1w = lds32_o<1024>(sA + beta * 4), y2w = lds32_o<2048>(sA + beta * 4), y3w = lds32_o<3072>(sA + beta * 4);
                    sts128(sU + beta * 16, bf2_add(y0w, bf2_mul(kv.x, d2)), bf2_add(y1w, bf2_mul(kv.y, d2)), bf2_add(y2w, bf2_mul(kv.z, d2)), bf2_add(y3w, bf2_mul(kv.w, d2)));
                }
            };
            auto conv_store = [&](int cp) {
                const int ch = cw * 4 + cp;
                fence_async_smem();
                __syncwarp();
                if (lane == 0) { bulk_s2g(p.y2T + (size_t)(cta * 8 + ch) * S + w * 512, sb + ST_U * B_STAGE + ch * U_PITCH + w * 1024, 1024); bulk_commit(); }
                if (cp & 1) { bar_sync(1 + cw, 128); if (wtid < 2) mbar_arrive_cta(bars + BAR_EMPTYB + 8 * (cp >> 1), wtid); }
            };
#pragma unroll 1
            for (int ci = 0; ci < 4; ci++) {
                const int k = 2 * ci + cw;
                float acc[128];
                bar_sync(5 + cw, 256);
                wg_fence();
                conv_issue<0>(acc, a, make_desc_noswz(sb + ST_U * B_STAGE + (cw * 4 + ci) * U_PITCH, 16, 128));
                wg_commit();
                if (k < 7) bar_arrive(5 + (cw ^ 1), 256);
                if (ci > 0) conv_finish(ci - 1);
                wg_wait<0>();
                if (ci > 0) conv_store(ci - 1);
                float f[16];
                {
                    float wv[34];
#pragma unroll
                    for (int i = 0; i < 16; i++) {
#pragma unroll
                        for (int jj = 0; jj < 2; jj++) {
                            const float ve = acc[8 * i + jj] + ((2 * i + 4 < 32) ? acc[4 * (2 * i + 4) + 2 + jj] : 0.f);
                            const float vo = acc[8 * i + 4 + jj] + ((2 * i + 5 < 32) ? acc[4 * (2 * i + 5) + 2 + jj] : 0.f);
                            const float vn = (i < 15) ? acc[8 * i + 8 + jj] + ((2 * i + 6 < 32) ? acc[4 * (2 * i + 6) + 2 + jj] : 0.f) : 0.f;
                            wv[2 * i + jj] = (b0 ? vn : ve) + __shfl_xor_sync(0xffffffffu, vo, 8);
                        }
                    }
                    wv[32] = wv[33] = 0.f;
#pragma unroll
                    for (int kk = 0; kk < 8; kk++)
#pragma unroll
                        for (int jj = 0; jj < 2; jj++)
                            f[2 * kk + jj] = (b1 ? wv[4 * kk + 4 + jj] : wv[4 * kk + jj]) + __shfl_xor_sync(0xffffffffu, wv[4 * kk + 2 + jj], 16);
                }
                {
                    const uint32_t sA = sb + (ci >> 1) * B_STAGE + ((ci & 1) * 2 + cw) * 8192;
#pragma unroll
                    for (int kk = 0; kk < 8; kk++) {
                        const float keep = podd ? f[2 * kk + 1] : f[2 * kk];
                        const float recv = __shfl_xor_sync(0xffffffffu, podd ? f[2 * kk] : f[2 * kk + 1], 4);
                        const uint32_t yw = pack_bf2(podd ? recv : keep, podd ? keep : recv);
                        asm volatile("st.shared.b32 [%0], %1;" :: "r"(sA + w * 1024 + (32 * kk + 8 * (r >> 1) + 2 * c4 + podd) * 4), "r"(yw) : "memory");
                    }
                }
                if (ci < 3) {
                    uint32_t hx[8];
                    conv_frag_addr(hx, sb + ((ci + 1) >> 1) * B_STAGE + (((ci + 1) & 1) * 2 + cw) * 8192 + cpy, w0, xb);
                    conv_load_a<0>(a, hx);
                    a[0][0] &= mask0;
                }
            }
            bar_sync(1 + cw, 128);
            conv_finish(3);
            conv_store(3);
        }
        {
            float acc[64];
            const int srow = m2 * 128 + cw * 64 + w * 16 + (lane >> 2);
            const uint2 st0 = __ldcg(p.stats + srow), st1 = __ldcg(p.stats + srow + 8);
            int i6 = 0, prev = 0; uint32_t rho = 0;
#pragma unroll 1
            for (int kb = 0; kb < 56; kb++) {
                const int sg = (0x513024 >> (4 * i6)) & 15;
                mbar_wait(bars + BAR_FULLB + 8 * sg, ((0x21u >> i6) & 1u) ^ rho);
                const uint64_t da = descA + sg * (B_STAGE >> 4), db = descB + sg * (B_STAGE >> 4);
                wg_fence();
                wgmma_128(acc, da, db, kb != 0);
#pragma unroll
                for (int k = 1; k < 4; k++) wgmma_128(acc, da + k * 2, db + k * 128, 1);
                wg_commit();
                if (kb == 0) {
                    if (lane == 0) bulk_wait_read();
                    bar_sync(1 + cw, 128);
                    if (wtid < 2) mbar_arrive_cta(bars + BAR_EMPTYB + 8 * ST_U, wtid);
                }
                if (kb == 8 && lane == 0) { bulk_wait_all(); flag_add_after_bulk(p.flags + (FL_Y + (cta >> 4)) * FLAG_STRIDE); }
                wg_wait<1>();
                if (kb > 0 && wtid < 2) mbar_arrive_cta(bars + BAR_EMPTYB + 8 * prev, wtid);
                prev = sg;
                if (++i6 == 6) { i6 = 0; rho ^= 1; }
            }
            cluster_arrive();
            mbar_wait(bars + BAR_OPFULL, 0);
            wg_wait<0>();
            mbar_wait(bars + BAR_FULLB + 0, 1);
            const float inv0 = __uint_as_float(st0.y), inv1 = __uint_as_float(st1.y);
            const uint32_t ycol = sb + OFF_STG + cw * 16384 + (((7 - 2 * w - ((lane >> 3) & 1)) ^ lrow7) << 4) + lrow7 * 128;
            const uint32_t xrow = sb + (cw * 64 + lrow) * 128;
#pragma unroll 1
            for (int g2 = 0; g2 < 2; g2++) {
#pragma unroll
                for (int hh = 0; hh < 4; hh++) {
                    const uint32_t grp = hh * 2 + lgrp;
                    const uint32_t xa = xrow + g2 * 16384 + ((grp ^ lrow7) << 4);
                    uint32_t x[4], y[4], o[4];
                    ldsm_x4(xa, x[0], x[1], x[2], x[3]);
                    ldsm_x4_t(ycol + (g2 * 8 + grp) * 1024, y[0], y[1], y[2], y[3]);
#pragma unroll
                    for (int i = 0; i < 4; i++) {
                        const uint32_t dd = bf2_sub(x[i], (i & 1) ? st1.x : st0.x);
                        const float iv = (i & 1) ? inv1 : inv0;
                        const uint32_t xn = pack_bf2(bf_lo(dd) * iv, bf_hi(dd) * iv);
                        o[i] = bf2_add(x[i], bf2_mul(bf2_mul(xn, y[i]), silu_bf2(pack_bf2(acc[8 * hh + 2 * i], acc[8 * hh + 2 * i + 1]))));
                    }
                    stsm_x4(xa, o[0], o[1], o[2], o[3]);
                }
#pragma unroll
                for (int i = 0; i < 32; i++) acc[i] = acc[i + 32];
                fence_async_smem();
                bar_sync(1 + cw, 128);
                if (wtid == 0) { tma_store_2d(&p.tmOut64, sb + g2 * 16384 + cw * 8192, n2 + g2 * 64, m2 * 128 + cw * 64); bulk_commit(); }
            }
            if (wtid == 0) bulk_wait_read();
        }
        cluster_wait_end();
    }
}

typedef CUresult (*EncodeTiledFn)(CUtensorMap*, CUtensorMapDataType, cuuint32_t, void*, const cuuint64_t*, const cuuint64_t*,
                                  const cuuint32_t*, const cuuint32_t*, CUtensorMapInterleave, CUtensorMapSwizzle,
                                  CUtensorMapL2promotion, CUtensorMapFloatOOBfill);

static void make_map(EncodeTiledFn enc, CUtensorMap* m, const void* ptr, int rank, const uint64_t* dims, const uint64_t* strides, const uint32_t* box,
                     CUtensorMapSwizzle swz = CU_TENSOR_MAP_SWIZZLE_128B) {
    cuuint64_t d[3], s[2];
    cuuint32_t b[3], es[3] = {1, 1, 1};
    for (int i = 0; i < rank; i++) { d[i] = dims[i]; b[i] = box[i]; }
    for (int i = 0; i + 1 < rank; i++) s[i] = strides[i];
    CUresult r = enc(m, CU_TENSOR_MAP_DATA_TYPE_BFLOAT16, rank, const_cast<void*>(ptr), d, s, b, es, CU_TENSOR_MAP_INTERLEAVE_NONE,
                     swz, CU_TENSOR_MAP_L2_PROMOTION_L2_128B, CU_TENSOR_MAP_FLOAT_OOB_FILL_NONE);
    if (r != CUDA_SUCCESS) fprintf(stderr, "cuTensorMapEncodeTiled failed: %d\n", (int)r);
}
static void map2d(EncodeTiledFn enc, CUtensorMap* m, const void* ptr, uint64_t cols, uint64_t rows, uint32_t box_rows) {
    const uint64_t d[2] = {cols, rows}, s[1] = {cols * 2};
    const uint32_t b[2] = {64, box_rows};
    make_map(enc, m, ptr, 2, d, s, b);
}
static void map3d(EncodeTiledFn enc, CUtensorMap* m, const void* ptr, uint64_t cols, uint64_t rows, uint32_t groups) {
    const uint64_t d[3] = {64, rows, cols / 64}, s[2] = {cols * 2, 128};
    const uint32_t b[3] = {64, 64, groups};
    make_map(enc, m, ptr, 3, d, s, b);
}

}

extern "C" void kernel_launch(void* const* d_in, const int* in_sizes, int n_in, void* d_out, int out_size) {
    using namespace h3;
    (void)in_sizes; (void)n_in; (void)out_size;
    static EncodeTiledFn enc = nullptr;
    static void *xn, *kvT, *hbuf, *y2T, *flags, *stats;
    if (!enc) {
        void* fn = nullptr;
        cudaDriverEntryPointQueryResult qr;
        cudaGetDriverEntryPoint("cuTensorMapEncodeTiled", &fn, cudaEnableDefault, &qr);
        enc = (EncodeTiledFn)fn;
        cudaGetSymbolAddress(&xn, g_xn);
        cudaGetSymbolAddress(&kvT, g_kvT);
        cudaGetSymbolAddress(&hbuf, g_h);
        cudaGetSymbolAddress(&y2T, g_y2T);
        cudaGetSymbolAddress(&flags, g_flags);
        cudaGetSymbolAddress(&stats, g_stats);
        cudaFuncSetAttribute(h3_kernel, cudaFuncAttributeMaxDynamicSharedMemorySize, SMEM_BYTES);
    }
    Params p;
    const bf16* q = (const bf16*)d_in[0];
    p.q = q; p.k = (const bf16*)d_in[1]; p.v = (const bf16*)d_in[2];
    p.shift_k = (const bf16*)d_in[3]; p.ssm_k = (const bf16*)d_in[4]; p.ssm_D = (const bf16*)d_in[5];
    const bf16* wg = (const bf16*)d_in[7];
    const bf16* wu = (const bf16*)d_in[8];
    const bf16* wd = (const bf16*)d_in[9];
    p.xn = (bf16*)xn; p.kvT = (bf16*)kvT; p.y2T = (bf16*)y2T; p.flags = (unsigned*)flags; p.stats = (uint2*)stats;
    map2d(enc, &p.tmXn128, xn, D, S, 128);
    map2d(enc, &p.tmXn64, xn, D, S, 64);
    map3d(enc, &p.tmWg2, wg, F, D, 2);
    map3d(enc, &p.tmWu2, wu, F, D, 2);
    map3d(enc, &p.tmWg1, wg, F, D, 1);
    map3d(enc, &p.tmWu1, wu, F, D, 1);
    map2d(enc, &p.tmH64, hbuf, F, S, 64);
    map3d(enc, &p.tmWd, wd, D, F, 2);
    map2d(enc, &p.tmX128, q, D, S, 128);
    map2d(enc, &p.tmY2T, y2T, S, D, 128);
    map2d(enc, &p.tmOut64, d_out, D, S, 64);
    {
        const uint64_t d[2] = {D, S}, st[1] = {D * 2};
        const uint32_t bk[2] = {128, 67}, bv[2] = {128, 64};
        make_map(enc, &p.tmK, p.k, 2, d, st, bk, CU_TENSOR_MAP_SWIZZLE_NONE);
        make_map(enc, &p.tmV, p.v, 2, d, st, bv, CU_TENSOR_MAP_SWIZZLE_NONE);
    }
    map2d(enc, &p.tmKvT, kvT, S, D, 128);

    cudaLaunchConfig_t cfg = {};
    cfg.gridDim = dim3(NCTA + 4);
    cfg.blockDim = dim3(384);
    cfg.dynamicSmemBytes = SMEM_BYTES;
    cfg.stream = cudaStreamPerThread;
    cudaLaunchAttribute at[1];
    at[0].id = cudaLaunchAttributeClusterDimension;
    at[0].val.clusterDim.x = 2; at[0].val.clusterDim.y = 1; at[0].val.clusterDim.z = 1;
    cfg.attrs = at; cfg.numAttrs = 1;
    cudaLaunchKernelEx(&cfg, h3_kernel, p);
}
```
